```python
import torch

def _softmax(x, axis=-1):
    return torch.softmax(x, dim=axis)
def _gelu(x):
    return torch.nn.functional.gelu(x, approximate="tanh")
def _silu(x):
    return torch.nn.functional.silu(x)
def _sigmoid(x):
    return torch.sigmoid(x)
def _layernorm(x, axis=-1, eps=1e-5):
    m = x.mean(dim=axis, keepdim=True)
    v = x.var(dim=axis, keepdim=True, unbiased=False)
    return (x - m) / torch.sqrt(v + eps)
def _scatter_add(tgt, idx, src, axis=0):
    return tgt.clone().index_add_(axis, idx, src)
def _segment_sum(src, seg, n):
    out = torch.zeros((n,) + src.shape[1:], dtype=src.dtype)
    return out.index_add_(0, seg, src)
def _pad(x, pw):
    flat = tuple(v for pair in reversed(pw) for v in pair)
    return torch.nn.functional.pad(x, flat)

kernel_name = 'gated_mix__spectral_fnet__dense_activation_relu__prompt'

def setup_inputs():

    _w = (lambda a: (lambda t: t.to(torch.bfloat16) if t.is_floating_point() else t)(torch.as_tensor(a)))
    def _A_setup():
        B, S, D = 1, 2048, 512
        ns = torch.arange(S)[:, None] * torch.arange(S)[None, :]
        nd = torch.arange(D)[:, None] * torch.arange(D)[None, :]
        Ws_re = torch.cos(-2.0 * torch.pi * ns / S).to(float)
        Ws_im = torch.sin(-2.0 * torch.pi * ns / S).to(float)
        Wd_re = torch.cos(-2.0 * torch.pi * nd / D).to(float)
        Wd_im = torch.sin(-2.0 * torch.pi * nd / D).to(float)
        return {
            "x": _w((lambda *s: torch.randn(*s, dtype=torch.bfloat16) * 0.05)(B, S, D)),
            "dft_seq_re": _w(Ws_re),
            "dft_seq_im": _w(Ws_im),
            "dft_hid_re": _w(Wd_re),
            "dft_hid_im": _w(Wd_im),
        }
    _A_in = _A_setup()

    def _B_setup():
        B, S, D, Dff = 1, 2048, 512, 1376
        return {
            "x": _w((lambda *s: torch.randn(*s, dtype=torch.bfloat16) * 0.05)(B, S, D)),
            "w1": _w((lambda *s: torch.randn(*s, dtype=torch.bfloat16) * 1.6)(D, Dff)),
            "w2": _w((lambda *s: torch.randn(*s, dtype=torch.bfloat16) * 1.6)(Dff, D)),
        }
    _B_in = _B_setup()

    return {
        "A_x": _A_in["x"],
        "A_dft_seq_re": _A_in["dft_seq_re"],
        "A_dft_seq_im": _A_in["dft_seq_im"],
        "A_dft_hid_re": _A_in["dft_hid_re"],
        "A_dft_hid_im": _A_in["dft_hid_im"],
        "B_x": _B_in["x"],
        "B_w1": _B_in["w1"],
        "B_w2": _B_in["w2"],
        "gate_w": _w((lambda *s: torch.randn(*s, dtype=torch.bfloat16) * 0.05)(512) * 16.0),
    }

def reference(A_x, A_dft_seq_re, A_dft_seq_im, A_dft_hid_re, A_dft_hid_im, B_x, B_w1, B_w2, gate_w):
    def _A_ref(x, dft_seq_re, dft_seq_im, dft_hid_re, dft_hid_im):
        a = torch.einsum("bsd,ed->bse", x, dft_hid_re)
        b = torch.einsum("bsd,ed->bse", x, dft_hid_im)
        y = torch.einsum("ts,bse->bte", dft_seq_re, a) - torch.einsum("ts,bse->bte", dft_seq_im, b)
        return y

    def _B_ref(x, w1, w2):
        h = torch.einsum("bsd,df->bsf", x, w1)
        zero = torch.zeros_like(h)
        h = torch.maximum(h, zero)
        return torch.einsum("bsf,fd->bsd", h, w2)

    x = A_x
    g = _sigmoid((x * gate_w).sum(-1, keepdims=True))
    a = _A_ref(x, A_dft_seq_re, A_dft_seq_im, A_dft_hid_re, A_dft_hid_im)
    b = _B_ref(x, B_w1, B_w2)
    return g * a + (1 - g) * b
```

```cpp
#include <cuda_runtime.h>
#include <cuda.h>
#include <cuda_bf16.h>
#include <stdint.h>

namespace {

constexpr int SEQ = 2048, DM = 512, DFF = 1376;
constexpr int NCTA = 128;
constexpr int NA = 6, NB = 4;
constexpr uint32_t A_BYTES = 16384, B_BYTES = 32768, P_BYTES = 24576;
constexpr uint32_t OFF_P = 8 * A_BYTES;
constexpr uint32_t OFF_BAR = OFF_P + 4 * P_BYTES;
constexpr uint32_t SMEM_BYTES = OFF_BAR + 512 + 1024;
__host__ __device__ constexpr uint32_t off_b(int s) { return s == 3 ? 6 * A_BYTES : OFF_P + s * B_BYTES; }
#define NTAIL 8
constexpr int NT = NTAIL;
static_assert(NT >= 4 && NT <= 8, "");
constexpr int HSL = 176;
constexpr int FG = 176;
constexpr uint32_t SPIN_LIMIT = 1u << 20;
constexpr uint32_t TAG_BIT = 0x10000u;

constexpr int BAR_FULL_A = 0, BAR_EMPTY_A = 6, BAR_FULL_X = 12;
constexpr int BAR_FULL_B = 14, BAR_EMPTY_B = 18, BAR_FULL_P = 22, BAR_EMPTY_P = 26, BAR_H_READY = 30;
constexpr int BAR_SIG_AB = 31, BAR_SIG_H = 32, BAR_AB_READY = 33, BAR_EPOCH = 34, BAR_XBUF = 35, BAR_XCHG = 36, BAR_B0 = 37;
constexpr int BAR_AB_T = 40;
constexpr uint32_t OFF_EPOCH = OFF_BAR + 8 * 48;

struct Params {
    CUtensorMap x, hr, hi, w1, cr, ci, w2;
    const __nv_bfloat16 *px, *phr, *phi, *pw1, *pcr, *pci, *pw2, *gate;
    __nv_bfloat16* pout;
};

__device__ uint4 g_ab[2 * 32 * 8 * 512];
__device__ uint4 g_h[16 * FG * 128];
__device__ uint4 g_part[NCTA * 8 * 256];
__device__ uint4 g_part2[NCTA * 4 * 256];
__device__ uint32_t g_cnt_ab[64 * 32];
__device__ uint32_t g_cnt_h[16 * 32];
__device__ uint32_t g_epoch[NCTA];
#define TL(i) do {} while (0)
#define TLG(i) do {} while (0)
#define TLC(i) do {} while (0)
#define TLC2(i) do {} while (0)
#define TLV(i, v) do { (void)(v); } while (0)

__device__ __forceinline__ uint32_t smem_u32(const void* p) { return (uint32_t)__cvta_generic_to_shared(p); }
__device__ __forceinline__ void mbar_init(uint32_t bar, uint32_t cnt) {
    asm volatile("mbarrier.init.shared::cta.b64 [%0], %1;" ::"r"(bar), "r"(cnt) : "memory");
}
__device__ __forceinline__ void mbar_expect_tx(uint32_t bar, uint32_t bytes) {
    asm volatile("mbarrier.arrive.expect_tx.shared::cta.b64 _, [%0], %1;" ::"r"(bar), "r"(bytes) : "memory");
}
__device__ __forceinline__ void mbar_arrive(uint32_t bar) {
    asm volatile("mbarrier.arrive.shared::cta.b64 _, [%0];" ::"r"(bar) : "memory");
}
__device__ __forceinline__ void mbar_arrive_n(uint32_t bar, uint32_t n) {
    asm volatile("mbarrier.arrive.shared::cta.b64 _, [%0], %1;" ::"r"(bar), "r"(n) : "memory");
}
__device__ __forceinline__ uint32_t mapa(uint32_t addr, uint32_t cta) {
    uint32_t r;
    asm volatile("mapa.shared::cluster.u32 %0, %1, %2;" : "=r"(r) : "r"(addr), "r"(cta));
    return r;
}
__device__ __forceinline__ void mbar_arrive_cluster(uint32_t remote_bar) {
    asm volatile("mbarrier.arrive.shared::cluster.b64 _, [%0];" ::"r"(remote_bar) : "memory");
}
__device__ __forceinline__ void mbar_wait(uint32_t bar, uint32_t parity) {
    asm volatile(
        "{\n.reg .pred p;\n.reg .u32 n;\n"
        "mbarrier.try_wait.parity.shared::cta.b64 p, [%0], %1;\n"
        "@p bra LAB_DONE;\n"
        "mov.u32 n, 0;\n"
        "LAB_WAIT:\n"
        "mbarrier.try_wait.parity.shared::cta.b64 p, [%0], %1;\n"
        "@p bra LAB_DONE;\n"
        "add.u32 n, n, 1;\nsetp.lt.u32 p, n, %2;\n@p bra LAB_WAIT;\ntrap;\n"
        "LAB_DONE:\n}\n" ::"r"(bar), "r"(parity), "n"(SPIN_LIMIT) : "memory");
}
__device__ __forceinline__ void mbar_wait_cluster(uint32_t bar, uint32_t parity) {
    asm volatile(
        "{\n.reg .pred p;\n.reg .u32 n;\nmov.u32 n, 0;\n"
        "LAB_WAIT:\n"
        "mbarrier.try_wait.parity.acquire.cluster.shared::cta.b64 p, [%0], %1;\n"
        "@p bra LAB_DONE;\n"
        "add.u32 n, n, 1;\nsetp.lt.u32 p, n, %2;\n@p bra LAB_WAIT;\ntrap;\n"
        "LAB_DONE:\n}\n" ::"r"(bar), "r"(parity), "n"(SPIN_LIMIT) : "memory");
}
__device__ __forceinline__ void tma_load_2d(uint32_t dst, const CUtensorMap* tm, int c0, int c1, uint32_t bar) {
    asm volatile("cp.async.bulk.tensor.2d.shared::cluster.global.mbarrier::complete_tx::bytes [%0], [%1, {%3, %4}], [%2];"
                 ::"r"(dst), "l"(tm), "r"(bar), "r"(c0), "r"(c1) : "memory");
}
__device__ __forceinline__ void tma_store_2d(const CUtensorMap* tm, int c0, int c1, uint32_t src) {
    asm volatile("cp.async.bulk.tensor.2d.global.shared::cta.bulk_group [%0, {%2, %3}], [%1];"
                 ::"l"(tm), "r"(src), "r"(c0), "r"(c1) : "memory");
}
__device__ __forceinline__ void bulk_load(uint32_t dst, const void* src, uint32_t bytes, uint32_t bar) {
    asm volatile("cp.async.bulk.shared::cluster.global.mbarrier::complete_tx::bytes [%0], [%1], %2, [%3];"
                 ::"r"(dst), "l"(src), "r"(bytes), "r"(bar) : "memory");
}
__device__ __forceinline__ void bulk_store(void* dst, uint32_t src, uint32_t bytes) {
    asm volatile("cp.async.bulk.global.shared::cta.bulk_group [%0], [%1], %2;" ::"l"(dst), "r"(src), "r"(bytes) : "memory");
}
__device__ __forceinline__ void stmatrix_x4(uint32_t addr, uint32_t a, uint32_t b, uint32_t c, uint32_t d) {
    asm volatile("stmatrix.sync.aligned.m8n8.x4.shared.b16 [%0], {%1, %2, %3, %4};" ::"r"(addr), "r"(a), "r"(b), "r"(c), "r"(d) : "memory");
}
__device__ __forceinline__ void l2_prefetch(const void* src, uint32_t bytes) {
    asm volatile("cp.async.bulk.prefetch.L2.global [%0], %1;" ::"l"(src), "r"(bytes) : "memory");
}
__device__ __forceinline__ void l2_prefetch_tile(const CUtensorMap* tm, int c0, int c1) {
    asm volatile("cp.async.bulk.prefetch.tensor.2d.L2.global [%0, {%1, %2}];" ::"l"(tm), "r"(c0), "r"(c1) : "memory");
}
__device__ __forceinline__ void prefetch_tmap(const CUtensorMap* tm) {
    asm volatile("prefetch.tensormap [%0];" ::"l"(tm) : "memory");
}
__device__ __forceinline__ void fence_proxy_async_global() { asm volatile("fence.proxy.async.global;" ::: "memory"); }
__device__ __forceinline__ void fence_proxy_async_smem() { asm volatile("fence.proxy.async.shared::cta;" ::: "memory"); }
__device__ __forceinline__ void red_release_add(uint32_t* p, uint32_t v) {
    asm volatile("red.release.gpu.global.add.u32 [%0], %1;" ::"l"(p), "r"(v) : "memory");
}
__device__ __forceinline__ void wait_counter(const uint32_t* p, uint32_t target) {
    asm volatile(
        "{\n.reg .pred p;\n.reg .u32 n;\n.reg .s32 v;\nmov.u32 n, 0;\n"
        "LAB_WAIT:\n"
        "ld.acquire.gpu.global.u32 v, [%0];\n"
        "sub.s32 v, v, %1;\nsetp.ge.s32 p, v, 0;\n"
        "@p bra LAB_DONE;\n"
        "add.u32 n, n, 1;\nsetp.lt.u32 p, n, %2;\n@p bra LAB_WAIT;\ntrap;\n"
        "LAB_DONE:\n}\n" ::"l"(p), "r"(target), "n"(SPIN_LIMIT) : "memory");
}
__device__ __forceinline__ uint32_t ld_acquire(const uint32_t* p) {
    uint32_t v;
    asm volatile("ld.acquire.gpu.global.u32 %0, [%1];" : "=r"(v) : "l"(p) : "memory");
    return v;
}
__device__ __forceinline__ void st_relaxed_v4(uint4* p, uint32_t a, uint32_t b, uint32_t c, uint32_t d) {
    asm volatile("st.relaxed.gpu.global.v4.b32 [%0], {%1, %2, %3, %4};" ::"l"(p), "r"(a), "r"(b), "r"(c), "r"(d) : "memory");
}
__device__ __forceinline__ uint4 ld_relaxed_v4(const uint4* p) {
    uint4 v;
    asm volatile("ld.relaxed.gpu.global.v4.b32 {%0, %1, %2, %3}, [%4];" : "=r"(v.x), "=r"(v.y), "=r"(v.z), "=r"(v.w) : "l"(p) : "memory");
    return v;
}
__device__ __forceinline__ uint32_t and3(uint32_t a, uint32_t b, uint32_t c) {
    uint32_t r;
    asm("lop3.b32 %0, %1, %2, %3, 0x80;" : "=r"(r) : "r"(a), "r"(b), "r"(c));
    return r;
}
__device__ __forceinline__ uint32_t eq3(uint32_t a, uint32_t b, uint32_t t) {
    uint32_t r;
    asm("lop3.b32 %0, %1, %2, %3, 0x81;" : "=r"(r) : "r"(a), "r"(b), "r"(t));
    return r;
}
__device__ __forceinline__ uint32_t fresh_bits(const uint4& v, uint32_t tag) { return eq3(v.x, v.y, tag) & eq3(v.z, v.w, tag); }
__device__ __forceinline__ uint32_t recv_tagged(uint4 (&rp)[4], const uint4* src, uint32_t tag) {
    uint32_t m = and3(fresh_bits(rp[0], tag), fresh_bits(rp[1], tag), fresh_bits(rp[2], tag) & fresh_bits(rp[3], tag));
    uint32_t n = 0;
    for (; !(m & TAG_BIT) && n < SPIN_LIMIT; n++) {
#pragma unroll
        for (int u = 0; u < 4; u++) {
            if (!(fresh_bits(rp[u], tag) & TAG_BIT)) rp[u] = ld_relaxed_v4(src + u * 256);
        }
        m = and3(fresh_bits(rp[0], tag), fresh_bits(rp[1], tag), fresh_bits(rp[2], tag) & fresh_bits(rp[3], tag));
    }
    __syncwarp();
    return n;
}
__device__ __forceinline__ float lo_f(uint32_t w) { return __uint_as_float(w << 16); }
__device__ __forceinline__ float hi_f(uint32_t w) { return __uint_as_float(w & 0xFFFE0000u); }
__device__ __forceinline__ uint32_t take_epoch(int slot) {
    uint32_t e = g_epoch[slot] + 1;
    g_epoch[slot] = e;
    return e;
}
__device__ __forceinline__ void wg_fence() { asm volatile("wgmma.fence.sync.aligned;" ::: "memory"); }
__device__ __forceinline__ void wg_commit() { asm volatile("wgmma.commit_group.sync.aligned;" ::: "memory"); }
template <int N>
__device__ __forceinline__ void wg_wait() { asm volatile("wgmma.wait_group.sync.aligned %0;" ::"n"(N) : "memory"); }
template <int N>
__device__ __forceinline__ void reg_fence(uint32_t (&d)[N]) {
#pragma unroll
    for (int i = 0; i < N; i++) asm volatile("" : "+r"(d[i])::"memory");
}
template <int N>
__device__ __forceinline__ void reg_fence(float (&d)[N]) {
#pragma unroll
    for (int i = 0; i < N; i++) asm volatile("" : "+f"(d[i])::"memory");
}
__host__ __device__ constexpr uint32_t desc_hi(uint32_t sbo, uint32_t swz) { return (sbo >> 4) | (swz << 30); }
__host__ __device__ constexpr uint32_t desc_off(uint32_t bytes, uint32_t lbo) { return (bytes >> 4) + ((lbo >> 4) << 16); }
__device__ __forceinline__ uint32_t pack_bf16(float lo, float hi) {
    uint32_t r;
    asm("cvt.rn.bf16x2.f32 %0, %1, %2;" : "=r"(r) : "f"(hi), "f"(lo));
    return r;
}
__device__ __forceinline__ uint32_t pack_bf16_relu(float lo, float hi) {
    uint32_t r;
    asm("cvt.rn.relu.bf16x2.f32 %0, %1, %2;" : "=r"(r) : "f"(hi), "f"(lo));
    return r;
}
__device__ __forceinline__ float round_bf16(float v) { return __bfloat162float(__float2bfloat16_rn(v)); }
__device__ __forceinline__ uint4 lds128(uint32_t addr) {
    uint4 v;
    asm volatile("ld.shared.v4.u32 {%0, %1, %2, %3}, [%4];" : "=r"(v.x), "=r"(v.y), "=r"(v.z), "=r"(v.w) : "r"(addr) : "memory");
    return v;
}
__device__ __forceinline__ float dot2_bf16(uint32_t a, uint32_t b) {
    uint32_t p;
    asm("mul.rn.bf16x2 %0, %1, %2;" : "=r"(p) : "r"(a), "r"(b));
    return __uint_as_float(p << 16) + __uint_as_float(p & 0xFFFF0000u);
}

template <int TB, uint32_t AHI, uint32_t BHI>
__device__ __forceinline__ void wgmma_n128(float (&d)[32], float (&e)[32], uint32_t alo, uint32_t blo, int scale_d) {
    asm volatile(
        "{\n.reg .pred p;\n.reg .b64 da, db;\n"
        "setp.ne.b32 p, %66, 0;\nmov.b64 da, {%64, %68};\nmov.b64 db, {%65, %69};\n"
        "wgmma.mma_async.sync.aligned.m64n128k16.f32.bf16.bf16 "
        "{%0, %1, %2, %3, %4, %5, %6, %7, %8, %9, %10, %11, %12, %13, %14, %15, "
        "%16, %17, %18, %19, %20, %21, %22, %23, %24, %25, %26, %27, %28, %29, %30, %31, "
        "%32, %33, %34, %35, %36, %37, %38, %39, %40, %41, %42, %43, %44, %45, %46, %47, "
        "%48, %49, %50, %51, %52, %53, %54, %55, %56, %57, %58, %59, %60, %61, %62, %63}, "
        "da, db, p, 1, 1, 0, %67;\n}\n"
        : "+f"(d[0]), "+f"(d[1]), "+f"(d[2]), "+f"(d[3]), "+f"(d[4]), "+f"(d[5]), "+f"(d[6]), "+f"(d[7]),
          "+f"(d[8]), "+f"(d[9]), "+f"(d[10]), "+f"(d[11]), "+f"(d[12]), "+f"(d[13]), "+f"(d[14]), "+f"(d[15]),
          "+f"(d[16]), "+f"(d[17]), "+f"(d[18]), "+f"(d[19]), "+f"(d[20]), "+f"(d[21]), "+f"(d[22]), "+f"(d[23]),
          "+f"(d[24]), "+f"(d[25]), "+f"(d[26]), "+f"(d[27]), "+f"(d[28]), "+f"(d[29]), "+f"(d[30]), "+f"(d[31]),
          "+f"(e[0]), "+f"(e[1]), "+f"(e[2]), "+f"(e[3]), "+f"(e[4]), "+f"(e[5]), "+f"(e[6]), "+f"(e[7]),
          "+f"(e[8]), "+f"(e[9]), "+f"(e[10]), "+f"(e[11]), "+f"(e[12]), "+f"(e[13]), "+f"(e[14]), "+f"(e[15]),
          "+f"(e[16]), "+f"(e[17]), "+f"(e[18]), "+f"(e[19]), "+f"(e[20]), "+f"(e[21]), "+f"(e[22]), "+f"(e[23]),
          "+f"(e[24]), "+f"(e[25]), "+f"(e[26]), "+f"(e[27]), "+f"(e[28]), "+f"(e[29]), "+f"(e[30]), "+f"(e[31])
        : "r"(alo), "r"(blo), "r"(scale_d), "n"(TB), "n"(AHI), "n"(BHI));
}

template <int TB, uint32_t AHI, uint32_t BHI>
__device__ __forceinline__ void wgmma_n136(float (&d)[68], uint32_t alo, uint32_t blo, int scale_d) {
    asm volatile(
        "{\n.reg .pred p;\n.reg .b64 da, db;\n"
        "setp.ne.b32 p, %70, 0;\nmov.b64 da, {%68, %72};\nmov.b64 db, {%69, %73};\n"
        "wgmma.mma_async.sync.aligned.m64n136k16.f32.bf16.bf16 "
        "{%0, %1, %2, %3, %4, %5, %6, %7, %8, %9, %10, %11, %12, %13, %14, %15, "
        "%16, %17, %18, %19, %20, %21, %22, %23, %24, %25, %26, %27, %28, %29, %30, %31, "
        "%32, %33, %34, %35, %36, %37, %38, %39, %40, %41, %42, %43, %44, %45, %46, %47, "
        "%48, %49, %50, %51, %52, %53, %54, %55, %56, %57, %58, %59, %60, %61, %62, %63, "
        "%64, %65, %66, %67}, "
        "da, db, p, 1, 1, 0, %71;\n}\n"
        : "+f"(d[0]), "+f"(d[1]), "+f"(d[2]), "+f"(d[3]), "+f"(d[4]), "+f"(d[5]), "+f"(d[6]), "+f"(d[7]),
          "+f"(d[8]), "+f"(d[9]), "+f"(d[10]), "+f"(d[11]), "+f"(d[12]), "+f"(d[13]), "+f"(d[14]), "+f"(d[15]),
          "+f"(d[16]), "+f"(d[17]), "+f"(d[18]), "+f"(d[19]), "+f"(d[20]), "+f"(d[21]), "+f"(d[22]), "+f"(d[23]),
          "+f"(d[24]), "+f"(d[25]), "+f"(d[26]), "+f"(d[27]), "+f"(d[28]), "+f"(d[29]), "+f"(d[30]), "+f"(d[31]),
          "+f"(d[32]), "+f"(d[33]), "+f"(d[34]), "+f"(d[35]), "+f"(d[36]), "+f"(d[37]), "+f"(d[38]), "+f"(d[39]),
          "+f"(d[40]), "+f"(d[41]), "+f"(d[42]), "+f"(d[43]), "+f"(d[44]), "+f"(d[45]), "+f"(d[46]), "+f"(d[47]),
          "+f"(d[48]), "+f"(d[49]), "+f"(d[50]), "+f"(d[51]), "+f"(d[52]), "+f"(d[53]), "+f"(d[54]), "+f"(d[55]),
          "+f"(d[56]), "+f"(d[57]), "+f"(d[58]), "+f"(d[59]), "+f"(d[60]), "+f"(d[61]), "+f"(d[62]), "+f"(d[63]),
          "+f"(d[64]), "+f"(d[65]), "+f"(d[66]), "+f"(d[67])
        : "r"(alo), "r"(blo), "r"(scale_d), "n"(TB), "n"(AHI), "n"(BHI));
}

template <int TB, uint32_t AHI, uint32_t BHI>
__device__ __forceinline__ void wgmma_n176(float (&d)[88], uint32_t alo, uint32_t blo, int scale_d) {
    asm volatile(
        "{\n.reg .pred p;\n.reg .b64 da, db;\n"
        "setp.ne.b32 p, %90, 0;\nmov.b64 da, {%88, %92};\nmov.b64 db, {%89, %93};\n"
        "wgmma.mma_async.sync.aligned.m64n176k16.f32.bf16.bf16 "
        "{%0, %1, %2, %3, %4, %5, %6, %7, %8, %9, %10, %11, %12, %13, %14, %15, "
        "%16, %17, %18, %19, %20, %21, %22, %23, %24, %25, %26, %27, %28, %29, %30, %31, "
        "%32, %33, %34, %35, %36, %37, %38, %39, %40, %41, %42, %43, %44, %45, %46, %47, "
        "%48, %49, %50, %51, %52, %53, %54, %55, %56, %57, %58, %59, %60, %61, %62, %63, "
        "%64, %65, %66, %67, %68, %69, %70, %71, %72, %73, %74, %75, %76, %77, %78, %79, "
        "%80, %81, %82, %83, %84, %85, %86, %87}, "
        "da, db, p, 1, 1, 0, %91;\n}\n"
        : "+f"(d[0]), "+f"(d[1]), "+f"(d[2]), "+f"(d[3]), "+f"(d[4]), "+f"(d[5]), "+f"(d[6]), "+f"(d[7]),
          "+f"(d[8]), "+f"(d[9]), "+f"(d[10]), "+f"(d[11]), "+f"(d[12]), "+f"(d[13]), "+f"(d[14]), "+f"(d[15]),
          "+f"(d[16]), "+f"(d[17]), "+f"(d[18]), "+f"(d[19]), "+f"(d[20]), "+f"(d[21]), "+f"(d[22]), "+f"(d[23]),
          "+f"(d[24]), "+f"(d[25]), "+f"(d[26]), "+f"(d[27]), "+f"(d[28]), "+f"(d[29]), "+f"(d[30]), "+f"(d[31]),
          "+f"(d[32]), "+f"(d[33]), "+f"(d[34]), "+f"(d[35]), "+f"(d[36]), "+f"(d[37]), "+f"(d[38]), "+f"(d[39]),
          "+f"(d[40]), "+f"(d[41]), "+f"(d[42]), "+f"(d[43]), "+f"(d[44]), "+f"(d[45]), "+f"(d[46]), "+f"(d[47]),
          "+f"(d[48]), "+f"(d[49]), "+f"(d[50]), "+f"(d[51]), "+f"(d[52]), "+f"(d[53]), "+f"(d[54]), "+f"(d[55]),
          "+f"(d[56]), "+f"(d[57]), "+f"(d[58]), "+f"(d[59]), "+f"(d[60]), "+f"(d[61]), "+f"(d[62]), "+f"(d[63]),
          "+f"(d[64]), "+f"(d[65]), "+f"(d[66]), "+f"(d[67]), "+f"(d[68]), "+f"(d[69]), "+f"(d[70]), "+f"(d[71]),
          "+f"(d[72]), "+f"(d[73]), "+f"(d[74]), "+f"(d[75]), "+f"(d[76]), "+f"(d[77]), "+f"(d[78]), "+f"(d[79]),
          "+f"(d[80]), "+f"(d[81]), "+f"(d[82]), "+f"(d[83]), "+f"(d[84]), "+f"(d[85]), "+f"(d[86]), "+f"(d[87])
        : "r"(alo), "r"(blo), "r"(scale_d), "n"(TB), "n"(AHI), "n"(BHI));
}

template <int TB, uint32_t AHI, uint32_t BHI>
__device__ __forceinline__ void wgmma_n256(float (&d)[32], float (&e)[32], float (&f)[64], uint32_t alo, uint32_t blo, int scale_d) {
    asm volatile(
        "{\n.reg .pred p;\n.reg .b64 da, db;\n"
        "setp.ne.b32 p, %130, 0;\nmov.b64 da, {%128, %132};\nmov.b64 db, {%129, %133};\n"
        "wgmma.mma_async.sync.aligned.m64n256k16.f32.bf16.bf16 "
        "{%0, %1, %2, %3, %4, %5, %6, %7, %8, %9, %10, %11, %12, %13, %14, %15, "
        "%16, %17, %18, %19, %20, %21, %22, %23, %24, %25, %26, %27, %28, %29, %30, %31, "
        "%32, %33, %34, %35, %36, %37, %38, %39, %40, %41, %42, %43, %44, %45, %46, %47, "
        "%48, %49, %50, %51, %52, %53, %54, %55, %56, %57, %58, %59, %60, %61, %62, %63, "
        "%64, %65, %66, %67, %68, %69, %70, %71, %72, %73, %74, %75, %76, %77, %78, %79, "
        "%80, %81, %82, %83, %84, %85, %86, %87, %88, %89, %90, %91, %92, %93, %94, %95, "
        "%96, %97, %98, %99, %100, %101, %102, %103, %104, %105, %106, %107, %108, %109, %110, %111, "
        "%112, %113, %114, %115, %116, %117, %118, %119, %120, %121, %122, %123, %124, %125, %126, %127}, "
        "da, db, p, 1, 1, 0, %131;\n}\n"
        : "+f"(d[0]), "+f"(d[1]), "+f"(d[2]), "+f"(d[3]), "+f"(d[4]), "+f"(d[5]), "+f"(d[6]), "+f"(d[7]),
          "+f"(d[8]), "+f"(d[9]), "+f"(d[10]), "+f"(d[11]), "+f"(d[12]), "+f"(d[13]), "+f"(d[14]), "+f"(d[15]),
          "+f"(d[16]), "+f"(d[17]), "+f"(d[18]), "+f"(d[19]), "+f"(d[20]), "+f"(d[21]), "+f"(d[22]), "+f"(d[23]),
          "+f"(d[24]), "+f"(d[25]), "+f"(d[26]), "+f"(d[27]), "+f"(d[28]), "+f"(d[29]), "+f"(d[30]), "+f"(d[31]),
          "+f"(e[0]), "+f"(e[1]), "+f"(e[2]), "+f"(e[3]), "+f"(e[4]), "+f"(e[5]), "+f"(e[6]), "+f"(e[7]),
          "+f"(e[8]), "+f"(e[9]), "+f"(e[10]), "+f"(e[11]), "+f"(e[12]), "+f"(e[13]), "+f"(e[14]), "+f"(e[15]),
          "+f"(e[16]), "+f"(e[17]), "+f"(e[18]), "+f"(e[19]), "+f"(e[20]), "+f"(e[21]), "+f"(e[22]), "+f"(e[23]),
          "+f"(e[24]), "+f"(e[25]), "+f"(e[26]), "+f"(e[27]), "+f"(e[28]), "+f"(e[29]), "+f"(e[30]), "+f"(e[31]),
          "+f"(f[0]), "+f"(f[1]), "+f"(f[2]), "+f"(f[3]), "+f"(f[4]), "+f"(f[5]), "+f"(f[6]), "+f"(f[7]),
          "+f"(f[8]), "+f"(f[9]), "+f"(f[10]), "+f"(f[11]), "+f"(f[12]), "+f"(f[13]), "+f"(f[14]), "+f"(f[15]),
          "+f"(f[16]), "+f"(f[17]), "+f"(f[18]), "+f"(f[19]), "+f"(f[20]), "+f"(f[21]), "+f"(f[22]), "+f"(f[23]),
          "+f"(f[24]), "+f"(f[25]), "+f"(f[26]), "+f"(f[27]), "+f"(f[28]), "+f"(f[29]), "+f"(f[30]), "+f"(f[31]),
          "+f"(f[32]), "+f"(f[33]), "+f"(f[34]), "+f"(f[35]), "+f"(f[36]), "+f"(f[37]), "+f"(f[38]), "+f"(f[39]),
          "+f"(f[40]), "+f"(f[41]), "+f"(f[42]), "+f"(f[43]), "+f"(f[44]), "+f"(f[45]), "+f"(f[46]), "+f"(f[47]),
          "+f"(f[48]), "+f"(f[49]), "+f"(f[50]), "+f"(f[51]), "+f"(f[52]), "+f"(f[53]), "+f"(f[54]), "+f"(f[55]),
          "+f"(f[56]), "+f"(f[57]), "+f"(f[58]), "+f"(f[59]), "+f"(f[60]), "+f"(f[61]), "+f"(f[62]), "+f"(f[63])
        : "r"(alo), "r"(blo), "r"(scale_d), "n"(TB), "n"(AHI), "n"(BHI));
}

#define DEFER_C 3
#define POLL_AT 3
#define POLL_NS 150
#define PF_START 1
#define FOLDSTEP 9
#define RODELAY 4
#define PDELAY 10
#define QDELAY 1000
#define ABSTEPS 2
#define ABSLOW 6
#define ABFAST 2
#define ABPRE 2
#define HSTEPS 6
#define PSLOTS 28
__host__ __device__ constexpr bool p1_is_ab(int s) { return s < 2 * (8 - NT) ? !(s & 1) : (s - 2 * (8 - NT) < NT); }
__host__ __device__ constexpr int p1_k(int s) {
    return s < 2 * (8 - NT) ? s / 2 : (s - 2 * (8 - NT) < NT ? s - (8 - NT) : s - 8);
}

template <int MAP>
__global__ void __cluster_dims__(2, 1, 1) __launch_bounds__(384, 1) fused_kernel(const __grid_constant__ Params p) {
    extern __shared__ uint8_t smem_raw[];
    const uint32_t base = (smem_u32(smem_raw) + 1023u) & ~1023u;
    const uint32_t bars = base + OFF_BAR;
    auto bar = [&](int i) { return bars + 8u * i; };
    const int warp = threadIdx.x >> 5, lane = threadIdx.x & 31;
    int role = blockIdx.x >> 1;
    if (MAP == 1) {
        const int c = role;
        const int g = c < 4 ? 0 : c < 36 ? (c - 4) & 7 : 1 + (c - 36) % 7;
        const int r = c < 4 ? 4 + c : c < 36 ? (c - 4) >> 3 : 4 + (c - 36) / 7;
        role = ((g & 1) * 8 + r) * 4 + (g >> 1);
    }
    const int bid = role * 2 + (blockIdx.x & 1);
    const int nh = bid & 1, kq = (bid >> 1) & 3, t = bid >> 3, j = bid & 7;
    const int kh = kq & 1, km = kq >> 1;
    const CUtensorMap* th = (j & 4) ? &p.hi : &p.hr;

    auto x_bar = [&](int f) { return bar(f < 6 ? BAR_FULL_A + f : BAR_FULL_X + f - 6); };
    auto x_fill = [&](int f) {
        mbar_expect_tx(x_bar(f), A_BYTES);
        tma_load_2d(base + f * A_BYTES, &p.x, 64 * f, 128 * t, x_bar(f));
    };
    auto p1_fill = [&](int f) {
        const uint32_t dst = base + OFF_P + (f & 3) * P_BYTES, fb = bar(BAR_FULL_P + (f & 3));
        const int kk = p1_k(f);
        if (p1_is_ab(f)) {
            mbar_expect_tx(fb, 16384 + 128);
            tma_load_2d(dst, th, 64 * kk, 128 * (j & 3), fb);
            bulk_load(dst + 16384, p.gate + 64 * kk, 128, fb);
        } else {
            mbar_expect_tx(fb, 24576);
            for (int q = 0; q < 3; q++) tma_load_2d(dst + q * 8192, &p.w1, HSL * j + 64 * q, 64 * kk, fb);
        }
    };

    if (threadIdx.x == 0) {
        TL(0); TLG(60);
        mbar_init(bar(BAR_FULL_A), 1); mbar_init(bar(BAR_FULL_P), 1);
        x_fill(0); p1_fill(0);
        TL(50);
    } else if (threadIdx.x == 32) {
        for (int i = 1; i < NA; i++) mbar_init(bar(BAR_FULL_A + i), 1);
        mbar_init(bar(BAR_FULL_X), 1); mbar_init(bar(BAR_FULL_X + 1), 1);
        for (int i = 1; i < 4; i++) mbar_init(bar(BAR_FULL_P + i), 1);
        for (int i = 0; i < NA; i++) mbar_init(bar(BAR_EMPTY_A + i), 8);
        for (int i = 0; i < 4; i++) {
            mbar_init(bar(BAR_EMPTY_P + i), 8);
            mbar_init(bar(BAR_FULL_B + i), 1); mbar_init(bar(BAR_EMPTY_B + i), 8);
        }
        prefetch_tmap(&p.w1);
    } else if (threadIdx.x == 64) {
        mbar_init(bar(BAR_SIG_AB), 8); mbar_init(bar(BAR_SIG_H), 8); mbar_init(bar(BAR_H_READY), 1);
        for (int i = 0; i < 8; i++) mbar_init(bar(BAR_AB_T + i), 1);
        mbar_init(bar(BAR_EPOCH), 1); mbar_init(bar(BAR_B0), 1);
    }
    __syncthreads();

    if (warp < 4) {
        asm volatile("setmaxnreg.dec.sync.aligned.u32 40;");
        if (warp == 0 && lane == 0) {
            if (NT == 8) { x_fill(1); p1_fill(1); x_fill(2); p1_fill(2); x_fill(3); p1_fill(3); }
            else { p1_fill(1); x_fill(1); p1_fill(2); p1_fill(3); x_fill(2); x_fill(3); }
#pragma unroll 1
            for (int f = 4; f < 8; f++) x_fill(f);
            const CUtensorMap* tc = km ? &p.ci : &p.cr;
            int slot = 0; uint32_t ph = 0;
#pragma unroll 1
            for (int i = 0; i < 27; i++) {
                const uint32_t dst = base + slot * A_BYTES, fb = bar(BAR_FULL_A + slot);
                if (i == DEFER_C) mbar_wait(bar(BAR_B0), 0);
                mbar_wait(bar(BAR_EMPTY_A + slot), ph);
                if (i < 16) {
                    mbar_expect_tx(fb, A_BYTES);
                    tma_load_2d(dst, tc, kh * 1024 + 64 * i, 128 * t, fb);
                } else {
                    if (i == 16) { mbar_wait(bar(BAR_H_READY), 0); fence_proxy_async_global(); TL(40); }
                    const uint32_t bytes = i < 26 ? A_BYTES : 12288u;
                    mbar_expect_tx(fb, bytes);
                    bulk_load(dst, g_h + (size_t)(t * FG + kh * 86 + 8 * (i - 16)) * 128, bytes, fb);
                }
                if (++slot == NA) { slot = 0; ph ^= 1; }
            }
        } else if (warp == 1 && lane == 0) {
#pragma unroll 1
            for (int f = 4; f < 16; f++) {
                mbar_wait(bar(BAR_EMPTY_P + (f & 3)), ((f >> 2) & 1) ^ 1);
                if (f >= 10) TL(112 + 2 * (f - 10));
                p1_fill(f);
                if (f >= 10) TL(113 + 2 * (f - 10));
            }
            TL(41);
#pragma unroll 1
            for (int f = 0; f < 22; f++) {
                const int bs = f & 3;
                const uint32_t dst = base + off_b(bs), fb = bar(BAR_FULL_B + bs);
                mbar_wait(bar(BAR_EMPTY_B + bs), (f >> 2) & 1);
                if (f < 16) {
                    if (!(f & 1)) { mbar_wait(bar(BAR_AB_T + (f >> 1)), 0); fence_proxy_async_global(); }
                    mbar_expect_tx(fb, B_BYTES);
                    const uint4* src = g_ab + (size_t)((km * 32 + kh * 16 + f) * 8 + nh * 4) * 512;
                    for (int q = 0; q < 4; q++) bulk_load(dst + q * 8192, src + (q ^ kq) * 512, 8192, fb);
                    if (f == 0) mbar_arrive(bar(BAR_B0));
                } else {
                    const int nsub = f < 21 ? 2 : 1;
                    mbar_expect_tx(fb, nsub * 16384);
                    for (int s = 0; s < nsub; s++)
                        for (int q = 0; q < 2; q++)
                            tma_load_2d(dst + s * 16384 + q * 8192, &p.w2, nh * 256 + (q ^ kq) * 64, kh * 688 + 128 * (f - 16) + 64 * s, fb);
                }
            }
        } else if (warp == 2 && lane == 0) {
            const uint32_t ep = take_epoch(bid);
            asm volatile("st.shared.u32 [%0], %1;" ::"r"(base + OFF_EPOCH), "r"(ep) : "memory");
            mbar_arrive(bar(BAR_EPOCH));
            prefetch_tmap(km ? &p.ci : &p.cr);
            prefetch_tmap(&p.w2);
            mbar_wait(bar(BAR_SIG_AB), 0);
            TL(46);
            fence_proxy_async_global();
            red_release_add(&g_cnt_ab[((j >> 1) * 16 + t) * 32], 1);
            TL(43);
            mbar_wait(bar(BAR_SIG_H), 0);
            fence_proxy_async_global();
            red_release_add(&g_cnt_h[t * 32], 1);
            wait_counter(&g_cnt_h[t * 32], 8 * ep);
            mbar_arrive(bar(BAR_H_READY));
            TL(44);
        } else if (warp == 3) {
            mbar_wait(bar(BAR_FULL_A + PF_START), 0);
            if (lane == 0) l2_prefetch((const uint8_t*)p.pw1 + bid * 11008, 11008);
            mbar_wait(bar(BAR_EPOCH), 0);
            uint32_t ep;
            asm volatile("ld.shared.u32 %0, [%1];" : "=r"(ep) : "r"(base + OFF_EPOCH) : "memory");
            const uint32_t* cnt = &g_cnt_ab[((km * 2 + nh) * 16 + kh * 8 + (lane & 7)) * 32];
            bool done = lane >= 8 || (int32_t)(ld_acquire(cnt) - 2 * ep) >= 0;
            if (done && lane < 8) mbar_arrive(bar(BAR_AB_T + lane));
            mbar_wait(bar(BAR_EMPTY_A + POLL_AT), 0);
            for (uint32_t n = 0; n < SPIN_LIMIT && !__all_sync(0xffffffffu, done); n++) {
                if (!done && (int32_t)(ld_acquire(cnt) - 2 * ep) >= 0) {
                    mbar_arrive(bar(BAR_AB_T + lane));
                    done = true;
                    if (lane == 0) TL(42);
                    if (lane == 7) TL(45);
                }
                __nanosleep(POLL_NS);
            }
            mbar_wait(bar(BAR_SIG_H), 0);
            if (lane == 0) l2_prefetch((const uint8_t*)p.pw2 + bid * 11008, 11008);
        }
    } else {
        asm volatile("setmaxnreg.inc.sync.aligned.u32 232;");
        const int w = __shfl_sync(0xffffffffu, (warp - 4) >> 2, 0), q = warp & 3, ctid = threadIdx.x - 128;
        constexpr uint32_t H_K128 = desc_hi(1024, 1);
        constexpr uint32_t H_MN128 = desc_hi(1024, 1);
        constexpr uint32_t H_AB = desc_hi(1024, 0);
        constexpr uint32_t H_H = desc_hi(128, 0);
        const uint32_t d0 = (base & 0x3FFFFu) >> 4;
        auto release = [&](int b) { if (lane == 0) mbar_arrive(bar(b)); };
        float g0, g1, o0, o1;
        float cO[32], cS[32], cX[64];
        uint32_t hpk[44];
        {
            float accAB[68], accH[88];
            float zz0 = 0.f, zz1 = 0.f;
            uint32_t* abdst = (uint32_t*)(g_ab + (size_t)(((j >> 2) * 32 + 2 * t + w) * 8 + (j & 3) * 2) * 512) + (2 * q) * 32 + lane;
            uint32_t abpk[32];
            const bool fast = (t & 7) < ABFAST;
            auto ab_store = [&](int slotno) {
#pragma unroll
                for (int e = 0; e < 32; e++) {
                    const bool inf = e * (4 * ABSTEPS + ABPRE) / 32 == slotno, ins = e * (4 * ABSLOW + ABPRE) / 32 == slotno;
                    if ((inf && ins) || (inf && fast) || (ins && !fast)) abdst[(e >> 1) * 256 + (e & 1) * 32] = abpk[e];
                }
            };
            TLC(52);
#pragma unroll
            for (int s = 0; s < 16; s++) {
                const int kk = p1_k(s);
                const bool isab = p1_is_ab(s);
                if (isab) mbar_wait(x_bar(kk), 0);
                mbar_wait(bar(BAR_FULL_P + (s & 3)), (s >> 2) & 1);
                TLC(20 + s);
                wg_fence();
#pragma unroll
                for (int i = 0; i < 4; i++) {
                    const uint32_t da = d0 + w * 512 + desc_off(kk * A_BYTES + i * 32, 16);
                    if (isab) wgmma_n136<0, H_K128, H_K128>(accAB, da, d0 + desc_off(OFF_P + (s & 3) * P_BYTES + i * 32, 16), (kk | i) != 0);
                    else wgmma_n176<1, H_K128, H_MN128>(accH, da, d0 + desc_off(OFF_P + (s & 3) * P_BYTES + i * 2048, 8192), (kk | i) != 0);
                    if (s >= 17 - NT && s < 17 - NT + ABSLOW) ab_store(ABPRE + (s - (17 - NT)) * 4 + i);
                }
                wg_commit();
                if ((s == 16 - NT + ABSTEPS && fast) || (s == 16 - NT + ABSLOW && !fast)) { __syncwarp(); release(BAR_SIG_AB); TLC(3); }
                if (s > 0) {
                    wg_wait<1>();
                    if (s - 1 < 12) release(BAR_EMPTY_P + ((s - 1) & 3));
                    if (s - 1 >= 13) release(BAR_EMPTY_B + (s - 1) - 13);
                    if (!p1_is_ab(s - 1) && p1_k(s - 1) < 6) release(BAR_EMPTY_A + p1_k(s - 1));
                }
                if (s == 16 - NT) {
                    TLC(2); if (warp == 4 && lane == 0) TLG(124);
                    reg_fence(accAB);
#pragma unroll
                    for (int e = 0; e < 32; e++) abpk[e] = pack_bf16(accAB[2 * e], accAB[2 * e + 1]);
                    zz0 = accAB[64]; zz1 = accAB[66];
                    reg_fence(abpk);
                    asm volatile("" : "+f"(zz0), "+f"(zz1)::"memory");
#pragma unroll
                    for (int u = 0; u < ABPRE; u++) ab_store(u);
                }
            }
            wg_wait<0>();
            TLC(4); if (warp == 4 && lane == 0) TLG(125);
            release(BAR_EMPTY_B + 2);
            release(BAR_EMPTY_B + 3);
            reg_fence(accH);
#pragma unroll
            for (int i = 0; i < 22; i++) {
                hpk[2 * i] = pack_bf16_relu(accH[4 * i], accH[4 * i + 1]);
                hpk[2 * i + 1] = pack_bf16_relu(accH[4 * i + 2], accH[4 * i + 3]);
            }
            reg_fence(hpk);
            const float z0 = round_bf16(__shfl_sync(0xffffffffu, zz0, lane & ~3));
            const float z1 = round_bf16(__shfl_sync(0xffffffffu, zz1, lane & ~3));
            g0 = round_bf16(__fdividef(1.f, 1.f + __expf(-z0)));
            g1 = round_bf16(__fdividef(1.f, 1.f + __expf(-z1)));
            o0 = round_bf16(1.f - g0); o1 = round_bf16(1.f - g1);
            TLC(5);
        }
        int sA = 0; uint32_t phA = 1;
        int pA = 0;
        mbar_wait(bar(BAR_EPOCH), 0);
        uint32_t tag;
        asm volatile("ld.shared.u32 %0, [%1];" : "=r"(tag) : "r"(base + OFF_EPOCH) : "memory");
        tag = (tag & 1u) << 16;
        uint4* pdst = g_part + (size_t)(bid ^ 4) * 2048 + ctid;
        uint4* qdst = g_part2 + (size_t)(bid ^ 2) * 1024 + ctid;
        uint4* pre = pdst;
        uint32_t* hdst = (uint32_t*)(g_h + (size_t)(t * FG + 22 * j) * 128) + (8 * w + 2 * q) * 32 + lane;
        auto c_step = [&](int i, bool trickle) {
            const uint32_t da = d0 + w * 512 + sA * (A_BYTES >> 4) + desc_off(0, 16), db = d0 + (off_b(i & 3) >> 4) + desc_off(0, 128);
            TLC(96 + i);
            mbar_wait(bar(BAR_FULL_A + sA), phA);
            mbar_wait(bar(BAR_FULL_B + (i & 3)), (i >> 2) & 1);
            TLC(64 + i);
            wg_fence();
#pragma unroll
            for (int u = 0; u < 4; u++) {
                wgmma_n256<1, H_K128, H_AB>(cO, cS, cX, da + u * 2, db + u * 16, (i | u) != 0);
                if (trickle) {
#pragma unroll
                    for (int e = 0; e < 44; e++)
                        if (e * (4 * HSTEPS) / 44 == i * 4 + u) hdst[(e >> 1) * 512 + (e & 1) * 32] = hpk[e];
                }
            }
            wg_commit();
            if (trickle && i == HSTEPS - 1) { __syncwarp(); release(BAR_SIG_H); }
            if (!trickle && i < HSTEPS + 6) {
                st_relaxed_v4(pre, tag ^ TAG_BIT, tag ^ TAG_BIT, tag ^ TAG_BIT, tag ^ TAG_BIT);
                st_relaxed_v4(pre + 256, tag ^ TAG_BIT, tag ^ TAG_BIT, tag ^ TAG_BIT, tag ^ TAG_BIT);
                pre = i == HSTEPS + 3 ? qdst : pre + 512;
            }
            if (i > 0) {
                wg_wait<1>();
                release(BAR_EMPTY_B + ((i - 1) & 3));
                release(BAR_EMPTY_A + pA);
            }
            pA = sA;
            if (++sA == NA) { sA = 0; phA ^= 1; }
        };
#pragma unroll
        for (int i = 0; i < HSTEPS; i++) c_step(i, true);
#pragma unroll 1
        for (int i = HSTEPS; i < 16; i++) c_step(i, false);
        float hO[32], hS[32];
        uint32_t xpk[32];
        uint4 rs[4], ro[4];
        const uint4* psrc = g_part + (size_t)bid * 2048 + ctid;
        const uint4* qsrc = g_part2 + (size_t)bid * 1024 + ctid;
        const float k0 = km ? -g0 : g0, k1 = km ? -g1 : g1;
        auto p_io = [&](int slotno) {
#pragma unroll
            for (int o = 0; o < 8; o++) {
                const int e = o ^ 4;
                if (o * PSLOTS / 8 == slotno) st_relaxed_v4(pdst + e * 256, xpk[4 * e], xpk[4 * e + 1], xpk[4 * e + 2], xpk[4 * e + 3]);
                if (o < 4 && o * PSLOTS / 8 + PDELAY == slotno) rs[o] = ld_relaxed_v4(psrc + e * 256);
                if (o >= 4 && 4 * (FOLDSTEP - 2) + 1 + RODELAY + 2 * (o - 4) == slotno) ro[o - 4] = ld_relaxed_v4(psrc + e * 256);
            }
        };
        auto fold4 = [&](float (&c)[32], int v, const uint4 (&r)[4]) {
            const uint32_t wa = (v & 1) ? r[v >> 1].z : r[v >> 1].x, wb = (v & 1) ? r[v >> 1].w : r[v >> 1].y;
            c[4 * v + 0] = k0 * (c[4 * v + 0] - lo_f(wa)); c[4 * v + 1] = k0 * (c[4 * v + 1] - hi_f(wa));
            c[4 * v + 2] = k1 * (c[4 * v + 2] - lo_f(wb)); c[4 * v + 3] = k1 * (c[4 * v + 3] - hi_f(wb));
#pragma unroll
            for (int u = 0; u < 4; u++) asm volatile("" : "+f"(c[4 * v + u])::"memory");
        };
        static_assert(3 * PSLOTS / 8 + PDELAY <= 4 * (FOLDSTEP - 2) && 4 * (FOLDSTEP - 2) + 7 + RODELAY <= 39 && FOLDSTEP <= 9, "");
#pragma unroll
        for (int i = 0; i < 11; i++) {
            const int fb = i >> 1;
            const uint32_t da = d0 + w * 64 + sA * (A_BYTES >> 4) + desc_off(0, 2048), db = d0 + desc_off(off_b(fb & 3) + (i & 1) * 16384, 8192);
            mbar_wait(bar(BAR_FULL_A + sA), phA);
            if (!(i & 1)) mbar_wait(bar(BAR_FULL_B + (fb & 3)), (fb >> 2) & 1);
            TLC(80 + i);
            wg_fence();
#pragma unroll
            for (int u = 0; u < (i < 10 ? 4 : 3); u++) {
                wgmma_n128<1, H_H, H_MN128>(hO, hS, da + u * 256, db + u * 128, (i | u) != 0);
                if (i > 0) p_io(1 + (i - 1) * 4 + u);
                if (i == FOLDSTEP - 1 || i == FOLDSTEP) fold4(cS, (i - FOLDSTEP + 1) * 4 + u, rs);
            }
            wg_commit();
            if (i == FOLDSTEP - 2) { TLC(14); const uint32_t nr = recv_tagged(rs, psrc + 4 * 256, tag); TLC(15); (void)nr; }
            if (i < 10) {
                wg_wait<1>();
                release(BAR_EMPTY_A + pA);
                if (!(i & 1)) release(BAR_EMPTY_B + ((fb - 1) & 3));
            }
            if (i == 0) {
                TLC(7); if (warp == 4 && lane == 0) TLG(126);
                TLC2(17);
                reg_fence(cO); reg_fence(cS); reg_fence(cX);
#pragma unroll
                for (int e = 0; e < 32; e++) xpk[e] = (pack_bf16(cX[2 * e], cX[2 * e + 1]) & ~TAG_BIT) | tag;
                reg_fence(xpk);
                p_io(0);
            }
            pA = sA;
            if (++sA == NA) { sA = 0; phA ^= 1; }
        }
        wg_wait<0>();
        TLC(10); if (warp == 4 && lane == 0) TLG(127);
        reg_fence(hO); reg_fence(hS);
        {
            const long long tq = clock64();
#pragma unroll
            for (int e = 0; e < 4; e++) {
                uint32_t v[4];
#pragma unroll
                for (int u = 0; u < 4; u++) {
                    const float o = (u & 1) ? o1 : o0;
                    v[u] = (pack_bf16(fmaf(o, hS[8 * e + 2 * u], cS[8 * e + 2 * u]), fmaf(o, hS[8 * e + 2 * u + 1], cS[8 * e + 2 * u + 1])) & ~TAG_BIT) | tag;
                }
                st_relaxed_v4(qdst + e * 256, v[0], v[1], v[2], v[3]);
            }
            TLC(11);
            recv_tagged(ro, psrc, tag);
#pragma unroll
            for (int v = 0; v < 8; v++) fold4(cO, v, ro);
#pragma unroll
            for (int u = 0; u < 32; u++) cO[u] = fmaf((u & 2) ? o1 : o0, hO[u], cO[u]);
            mbar_wait(bar(BAR_EMPTY_B + 2), 1);
            while (clock64() - tq < QDELAY) {}
#pragma unroll
            for (int u = 0; u < 4; u++) rs[u] = ld_relaxed_v4(qsrc + u * 256);
            TLC(9); recv_tagged(rs, qsrc, tag);
            TLC(12);
            uint32_t pk[16];
#pragma unroll
            for (int u = 0; u < 4; u++) {
                pk[4 * u + 0] = pack_bf16(cO[8 * u + 0] + lo_f(rs[u].x), cO[8 * u + 1] + hi_f(rs[u].x));
                pk[4 * u + 1] = pack_bf16(cO[8 * u + 2] + lo_f(rs[u].y), cO[8 * u + 3] + hi_f(rs[u].y));
                pk[4 * u + 2] = pack_bf16(cO[8 * u + 4] + lo_f(rs[u].z), cO[8 * u + 5] + hi_f(rs[u].z));
                pk[4 * u + 3] = pack_bf16(cO[8 * u + 6] + lo_f(rs[u].w), cO[8 * u + 7] + hi_f(rs[u].w));
            }
            const uint32_t stg = base + off_b(2) + (warp - 4) * 2048;
            const int row = ((lane >> 3) & 1) * 8 + (lane & 7);
#pragma unroll
            for (int u = 0; u < 4; u++) {
                const int c = 2 * u + (lane >> 4);
                stmatrix_x4(stg + row * 128 + ((c ^ (row & 7)) << 4), pk[4 * u], pk[4 * u + 1], pk[4 * u + 2], pk[4 * u + 3]);
            }
            __syncwarp();
            uint4* orow = (uint4*)(p.pout + (size_t)(128 * t + 64 * w + 16 * q + (lane >> 3)) * DM + nh * 256 + kq * 64) + (lane & 7);
#pragma unroll
            for (int u = 0; u < 4; u++) {
                const int r = 4 * u + (lane >> 3);
                orow[u * 4 * (DM / 8)] = lds128(stg + r * 128 + (((lane & 7) ^ (r & 7)) << 4));
            }
            TLC(13);
            if (warp == 4 && lane == 0) TLG(61);
        }
    }
}

__device__ __nv_bfloat16 g_fb[SEQ * (2 * DM + DFF)];
__global__ void fb_stage1(const __nv_bfloat16* x, const __nv_bfloat16* hr, const __nv_bfloat16* hi, const __nv_bfloat16* w1) {
    __shared__ float xs[DM];
    const int r = blockIdx.x;
    for (int d = threadIdx.x; d < DM; d += blockDim.x) xs[d] = __bfloat162float(x[r * DM + d]);
    __syncthreads();
    for (int c = threadIdx.x; c < 2 * DM + DFF; c += blockDim.x) {
        float s = 0.f;
        if (c < 2 * DM) {
            const __nv_bfloat16* m = (c < DM ? hr : hi) + (c & (DM - 1)) * DM;
            for (int d = 0; d < DM; d++) s += xs[d] * __bfloat162float(m[d]);
        } else {
            for (int d = 0; d < DM; d++) s += xs[d] * __bfloat162float(w1[d * DFF + c - 2 * DM]);
            s = fmaxf(s, 0.f);
        }
        g_fb[(size_t)r * (2 * DM + DFF) + c] = __float2bfloat16_rn(s);
    }
}
__global__ void fb_stage2(const __nv_bfloat16* x, const __nv_bfloat16* cr, const __nv_bfloat16* ci, const __nv_bfloat16* w2,
                          const __nv_bfloat16* gate, __nv_bfloat16* out) {
    const int r = blockIdx.x, c = threadIdx.x;
    float z = 0.f, y = 0.f, f = 0.f;
    for (int d = 0; d < DM; d++) z += __bfloat162float(x[r * DM + d]) * __bfloat162float(gate[d]);
    for (int s = 0; s < SEQ; s++) {
        const __nv_bfloat16* ab = g_fb + (size_t)s * (2 * DM + DFF);
        y += __bfloat162float(cr[(size_t)r * SEQ + s]) * __bfloat162float(ab[c]) - __bfloat162float(ci[(size_t)r * SEQ + s]) * __bfloat162float(ab[DM + c]);
    }
    for (int k = 0; k < DFF; k++) f += __bfloat162float(g_fb[(size_t)r * (2 * DM + DFF) + 2 * DM + k]) * __bfloat162float(w2[k * DM + c]);
    const float g = 1.f / (1.f + __expf(-z));
    out[r * DM + c] = __float2bfloat16_rn(g * y + (1.f - g) * f);
}
__global__ void probe_kernel() {}

typedef CUresult (*EncodeFn)(CUtensorMap*, CUtensorMapDataType, cuuint32_t, void*, const cuuint64_t*, const cuuint64_t*,
                             const cuuint32_t*, const cuuint32_t*, CUtensorMapInterleave, CUtensorMapSwizzle,
                             CUtensorMapL2promotion, CUtensorMapFloatOOBfill);

bool make_map(EncodeFn enc, CUtensorMap* m, const void* ptr, uint64_t inner, uint64_t outer, uint32_t box_inner, uint32_t box_outer) {
    cuuint64_t dims[2] = {inner, outer};
    cuuint64_t strides[1] = {inner * 2};
    cuuint32_t box[2] = {box_inner, box_outer};
    cuuint32_t es[2] = {1, 1};
    return enc(m, CU_TENSOR_MAP_DATA_TYPE_BFLOAT16, 2, const_cast<void*>(ptr), dims, strides, box, es, CU_TENSOR_MAP_INTERLEAVE_NONE,
               CU_TENSOR_MAP_SWIZZLE_128B, CU_TENSOR_MAP_L2_PROMOTION_L2_128B, CU_TENSOR_MAP_FLOAT_OOB_FILL_NONE) == CUDA_SUCCESS;
}

template <class K>
int max_clusters(K kernel, int cluster, bool set_dim) {
    cudaLaunchConfig_t cfg = {};
    cfg.gridDim = dim3(NCTA);
    cfg.blockDim = dim3(384);
    cfg.dynamicSmemBytes = SMEM_BYTES;
    cudaLaunchAttribute at[1];
    at[0].id = cudaLaunchAttributeClusterDimension;
    at[0].val.clusterDim.x = cluster;
    at[0].val.clusterDim.y = 1;
    at[0].val.clusterDim.z = 1;
    cfg.attrs = at;
    cfg.numAttrs = set_dim ? 1 : 0;
    int n = 0;
    if (cudaOccupancyMaxActiveClusters(&n, kernel, &cfg) != cudaSuccess) { (void)cudaGetLastError(); return 0; }
    return n;
}

}

extern "C" void kernel_launch(void* const* d_in, const int* in_sizes, int n_in, void* d_out, int out_size) {
    (void)in_sizes; (void)n_in; (void)out_size;
    static Params prm;
    static const void* cached[10] = {};
    static int mode = -1;
    bool same = mode >= 0 && cached[9] == d_out;
    for (int i = 0; i < 9; i++) same = same && cached[i] == d_in[i];
    if (!same) {
        prm.px = (const __nv_bfloat16*)d_in[0];
        prm.pcr = (const __nv_bfloat16*)d_in[1];
        prm.pci = (const __nv_bfloat16*)d_in[2];
        prm.phr = (const __nv_bfloat16*)d_in[3];
        prm.phi = (const __nv_bfloat16*)d_in[4];
        prm.pw1 = (const __nv_bfloat16*)d_in[6];
        prm.pw2 = (const __nv_bfloat16*)d_in[7];
        prm.gate = (const __nv_bfloat16*)d_in[8];
        prm.pout = (__nv_bfloat16*)d_out;
        void* fn = nullptr;
        cudaDriverEntryPointQueryResult qr;
        bool ok = cudaGetDriverEntryPoint("cuTensorMapEncodeTiled", &fn, cudaEnableDefault, &qr) == cudaSuccess && fn != nullptr;
        EncodeFn enc = (EncodeFn)fn;
        ok = ok && make_map(enc, &prm.x, prm.px, DM, SEQ, 64, 128) && make_map(enc, &prm.hr, prm.phr, DM, DM, 64, 128) &&
             make_map(enc, &prm.hi, prm.phi, DM, DM, 64, 128) && make_map(enc, &prm.w1, prm.pw1, DFF, DM, 64, 64) &&
             make_map(enc, &prm.cr, prm.pcr, SEQ, SEQ, 64, 128) && make_map(enc, &prm.ci, prm.pci, SEQ, SEQ, 64, 128) &&
             make_map(enc, &prm.w2, prm.pw2, DM, DFF, 64, 64);
        ok = ok && cudaFuncSetAttribute(fused_kernel<0>, cudaFuncAttributeMaxDynamicSharedMemorySize, SMEM_BYTES) == cudaSuccess &&
             cudaFuncSetAttribute(fused_kernel<1>, cudaFuncAttributeMaxDynamicSharedMemorySize, SMEM_BYTES) == cudaSuccess &&
             cudaFuncSetAttribute(probe_kernel, cudaFuncAttributeMaxDynamicSharedMemorySize, SMEM_BYTES) == cudaSuccess;
        ok = ok && max_clusters(fused_kernel<0>, 2, false) >= NCTA / 2;
        (void)cudaGetLastError();
        mode = !ok ? 2 : (max_clusters(probe_kernel, 2, true) == 66 && max_clusters(probe_kernel, 4, true) == 30 && max_clusters(probe_kernel, 8, true) == 15) ? 1 : 0;
        for (int i = 0; i < 9; i++) cached[i] = d_in[i];
        cached[9] = d_out;
    }
    if (mode == 1) {
        fused_kernel<1><<<NCTA, 384, SMEM_BYTES>>>(prm);
    } else if (mode == 0) {
        fused_kernel<0><<<NCTA, 384, SMEM_BYTES>>>(prm);
    } else {
        fb_stage1<<<SEQ, 256>>>(prm.px, prm.phr, prm.phi, prm.pw1);
        fb_stage2<<<SEQ, DM>>>(prm.px, prm.pcr, prm.pci, prm.pw2, prm.gate, prm.pout);
    }
}
```

```cpp
#include <cuda_runtime.h>
#include <cuda.h>
#include <cuda_bf16.h>
#include <stdint.h>

namespace {

constexpr int SEQ = 2048, DM = 512, DFF = 1376;
constexpr int NCTA = 128;
constexpr int NA = 6;
constexpr uint32_t A_BYTES = 16384, B_BYTES = 32768, P_BYTES = 24576;
constexpr uint32_t OFF_P = 8 * A_BYTES;
constexpr uint32_t OFF_BAR = OFF_P + 4 * P_BYTES;
constexpr uint32_t OFF_EPOCH = OFF_BAR + 8 * 48;
constexpr uint32_t SMEM_BYTES = OFF_BAR + 512 + 1024;
__host__ __device__ constexpr uint32_t off_b(int s) { return s == 3 ? 6 * A_BYTES : OFF_P + s * B_BYTES; }
constexpr int HSL = 176;
constexpr int FG = 176;
constexpr uint32_t SPIN_LIMIT = 1u << 20;
constexpr uint32_t TAG_BIT = 0x10000u;

constexpr int BAR_FULL_A = 0, BAR_EMPTY_A = 6, BAR_FULL_X = 12, BAR_FULL_B = 14, BAR_EMPTY_B = 18, BAR_FULL_P = 22, BAR_EMPTY_P = 26;
constexpr int BAR_H_READY = 30, BAR_SIG_AB = 31, BAR_SIG_H = 32, BAR_EPOCH = 33, BAR_B0 = 34;
constexpr int BAR_AB_T = 40;

constexpr int AB_PRE = 2, AB_FAST_STEPS = 4, AB_SLOW_STEPS = 6, AB_FAST_TILES = 2;
constexpr int H_START = 1, H_STEPS = 8, ZERO_STEP = 2;
constexpr int X_SLOTS = 28, X_DELAY = 16, X_LOAD2 = 33;
constexpr int DEFER_A = 3, POLL_AT = 3, POLL_NS = 50;

struct Params {
    CUtensorMap x, hr, hi, gw, w1, cr, ci, w2;
    const __nv_bfloat16 *px, *phr, *phi, *pw1, *pcr, *pci, *pw2, *gate;
    __nv_bfloat16* pout;
};

__device__ uint4 g_ab[2 * 32 * 8 * 512];
__device__ uint4 g_h[16 * FG * 128];
__device__ uint4 g_part[NCTA * 8 * 256];
__device__ uint32_t g_cnt_ab[64 * 32];
__device__ uint32_t g_cnt_h[16 * 32];
__device__ uint32_t g_epoch[NCTA];

__device__ __forceinline__ uint32_t smem_u32(const void* p) { return (uint32_t)__cvta_generic_to_shared(p); }
__device__ __forceinline__ void mbar_init(uint32_t bar, uint32_t cnt) {
    asm volatile("mbarrier.init.shared::cta.b64 [%0], %1;" ::"r"(bar), "r"(cnt) : "memory");
}
__device__ __forceinline__ void mbar_expect_tx(uint32_t bar, uint32_t bytes) {
    asm volatile("mbarrier.arrive.expect_tx.shared::cta.b64 _, [%0], %1;" ::"r"(bar), "r"(bytes) : "memory");
}
__device__ __forceinline__ void mbar_arrive(uint32_t bar) {
    asm volatile("mbarrier.arrive.shared::cta.b64 _, [%0];" ::"r"(bar) : "memory");
}
__device__ __forceinline__ void mbar_wait(uint32_t bar, uint32_t parity) {
    asm volatile(
        "{\n.reg .pred p;\n.reg .u32 n;\n"
        "mbarrier.try_wait.parity.shared::cta.b64 p, [%0], %1;\n"
        "@p bra LAB_DONE;\n"
        "mov.u32 n, 0;\n"
        "LAB_WAIT:\n"
        "mbarrier.try_wait.parity.shared::cta.b64 p, [%0], %1;\n"
        "@p bra LAB_DONE;\n"
        "add.u32 n, n, 1;\nsetp.lt.u32 p, n, %2;\n@p bra LAB_WAIT;\ntrap;\n"
        "LAB_DONE:\n}\n" ::"r"(bar), "r"(parity), "n"(SPIN_LIMIT) : "memory");
}
__device__ __forceinline__ void wait_counter(const uint32_t* p, uint32_t target) {
    asm volatile(
        "{\n.reg .pred p;\n.reg .u32 n;\n.reg .s32 v;\nmov.u32 n, 0;\n"
        "LAB_WAIT:\n"
        "ld.acquire.gpu.global.u32 v, [%0];\n"
        "sub.s32 v, v, %1;\nsetp.ge.s32 p, v, 0;\n"
        "@p bra LAB_DONE;\n"
        "add.u32 n, n, 1;\nsetp.lt.u32 p, n, %2;\n@p bra LAB_WAIT;\ntrap;\n"
        "LAB_DONE:\n}\n" ::"l"(p), "r"(target), "n"(SPIN_LIMIT) : "memory");
}
__device__ __forceinline__ void tma_load_2d(uint32_t dst, const CUtensorMap* tm, int c0, int c1, uint32_t bar) {
    asm volatile("cp.async.bulk.tensor.2d.shared::cluster.global.mbarrier::complete_tx::bytes [%0], [%1, {%3, %4}], [%2];"
                 ::"r"(dst), "l"(tm), "r"(bar), "r"(c0), "r"(c1) : "memory");
}
__device__ __forceinline__ void bulk_load(uint32_t dst, const void* src, uint32_t bytes, uint32_t bar) {
    asm volatile("cp.async.bulk.shared::cluster.global.mbarrier::complete_tx::bytes [%0], [%1], %2, [%3];"
                 ::"r"(dst), "l"(src), "r"(bytes), "r"(bar) : "memory");
}
__device__ __forceinline__ void l2_prefetch(const void* src, uint32_t bytes) {
    asm volatile("cp.async.bulk.prefetch.L2.global [%0], %1;" ::"l"(src), "r"(bytes) : "memory");
}
__device__ __forceinline__ void l2_prefetch_tile(const CUtensorMap* tm, int c0, int c1) {
    asm volatile("cp.async.bulk.prefetch.tensor.2d.L2.global [%0, {%1, %2}];" ::"l"(tm), "r"(c0), "r"(c1) : "memory");
}
__device__ __forceinline__ void prefetch_tmap(const CUtensorMap* tm) {
    asm volatile("prefetch.tensormap [%0];" ::"l"(tm) : "memory");
}
__device__ __forceinline__ void fence_proxy_async_global() { asm volatile("fence.proxy.async.global;" ::: "memory"); }
__device__ __forceinline__ void red_release_add(uint32_t* p, uint32_t v) {
    asm volatile("red.release.gpu.global.add.u32 [%0], %1;" ::"l"(p), "r"(v) : "memory");
}
__device__ __forceinline__ uint32_t ld_acquire(const uint32_t* p) {
    uint32_t v;
    asm volatile("ld.acquire.gpu.global.u32 %0, [%1];" : "=r"(v) : "l"(p) : "memory");
    return v;
}
__device__ __forceinline__ void st_relaxed_v4(uint4* p, uint32_t a, uint32_t b, uint32_t c, uint32_t d) {
    asm volatile("st.relaxed.gpu.global.v4.b32 [%0], {%1, %2, %3, %4};" ::"l"(p), "r"(a), "r"(b), "r"(c), "r"(d) : "memory");
}
__device__ __forceinline__ uint4 ld_relaxed_v4(const uint4* p) {
    uint4 v;
    asm volatile("ld.relaxed.gpu.global.v4.b32 {%0, %1, %2, %3}, [%4];" : "=r"(v.x), "=r"(v.y), "=r"(v.z), "=r"(v.w) : "l"(p) : "memory");
    return v;
}
__device__ __forceinline__ uint4 lds128(uint32_t addr) {
    uint4 v;
    asm volatile("ld.shared.v4.u32 {%0, %1, %2, %3}, [%4];" : "=r"(v.x), "=r"(v.y), "=r"(v.z), "=r"(v.w) : "r"(addr) : "memory");
    return v;
}
__device__ __forceinline__ void stmatrix_x4(uint32_t addr, uint32_t a, uint32_t b, uint32_t c, uint32_t d) {
    asm volatile("stmatrix.sync.aligned.m8n8.x4.shared.b16 [%0], {%1, %2, %3, %4};" ::"r"(addr), "r"(a), "r"(b), "r"(c), "r"(d) : "memory");
}
__device__ __forceinline__ uint32_t and3(uint32_t a, uint32_t b, uint32_t c) {
    uint32_t r;
    asm("lop3.b32 %0, %1, %2, %3, 0x80;" : "=r"(r) : "r"(a), "r"(b), "r"(c));
    return r;
}
__device__ __forceinline__ uint32_t eq3(uint32_t a, uint32_t b, uint32_t t) {
    uint32_t r;
    asm("lop3.b32 %0, %1, %2, %3, 0x81;" : "=r"(r) : "r"(a), "r"(b), "r"(t));
    return r;
}
__device__ __forceinline__ uint32_t fresh_bits(const uint4& v, uint32_t tag) { return eq3(v.x, v.y, tag) & eq3(v.z, v.w, tag); }
__device__ __forceinline__ void recv_tagged(uint4 (&rp)[4], const uint4* src, uint32_t tag) {
    uint32_t m = and3(fresh_bits(rp[0], tag), fresh_bits(rp[1], tag), fresh_bits(rp[2], tag) & fresh_bits(rp[3], tag));
    for (uint32_t n = 0; !(m & TAG_BIT) && n < SPIN_LIMIT; n++) {
#pragma unroll
        for (int u = 0; u < 4; u++) {
            if (!(fresh_bits(rp[u], tag) & TAG_BIT)) rp[u] = ld_relaxed_v4(src + u * 256);
        }
        m = and3(fresh_bits(rp[0], tag), fresh_bits(rp[1], tag), fresh_bits(rp[2], tag) & fresh_bits(rp[3], tag));
    }
    __syncwarp();
}
__device__ __forceinline__ float lo_f(uint32_t w) { return __uint_as_float(w << 16); }
__device__ __forceinline__ float hi_f(uint32_t w) { return __uint_as_float(w & 0xFFFE0000u); }
__device__ __forceinline__ void wg_fence() { asm volatile("wgmma.fence.sync.aligned;" ::: "memory"); }
__device__ __forceinline__ void wg_commit() { asm volatile("wgmma.commit_group.sync.aligned;" ::: "memory"); }
template <int N>
__device__ __forceinline__ void wg_wait() { asm volatile("wgmma.wait_group.sync.aligned %0;" ::"n"(N) : "memory"); }
template <int N>
__device__ __forceinline__ void reg_fence(uint32_t (&d)[N]) {
#pragma unroll
    for (int i = 0; i < N; i++) asm volatile("" : "+r"(d[i])::"memory");
}
template <int N>
__device__ __forceinline__ void reg_fence(float (&d)[N]) {
#pragma unroll
    for (int i = 0; i < N; i++) asm volatile("" : "+f"(d[i])::"memory");
}
__host__ __device__ constexpr uint32_t desc_hi(uint32_t sbo, uint32_t swz) { return (sbo >> 4) | (swz << 30); }
__host__ __device__ constexpr uint32_t desc_off(uint32_t bytes, uint32_t lbo) { return (bytes >> 4) + ((lbo >> 4) << 16); }
__device__ __forceinline__ uint32_t pack_bf16(float lo, float hi) {
    uint32_t r;
    asm("cvt.rn.bf16x2.f32 %0, %1, %2;" : "=r"(r) : "f"(hi), "f"(lo));
    return r;
}
__device__ __forceinline__ uint32_t pack_bf16_relu(float lo, float hi) {
    uint32_t r;
    asm("cvt.rn.relu.bf16x2.f32 %0, %1, %2;" : "=r"(r) : "f"(hi), "f"(lo));
    return r;
}
__device__ __forceinline__ float round_bf16(float v) { return __bfloat162float(__float2bfloat16_rn(v)); }

template <int TB, uint32_t AHI, uint32_t BHI>
__device__ __forceinline__ void wgmma_n128(float (&d)[32], float (&e)[32], uint32_t alo, uint32_t blo, int scale_d) {
    asm volatile(
        "{\n.reg .pred p;\n.reg .b64 da, db;\n"
        "setp.ne.b32 p, %66, 0;\nmov.b64 da, {%64, %68};\nmov.b64 db, {%65, %69};\n"
        "wgmma.mma_async.sync.aligned.m64n128k16.f32.bf16.bf16 "
        "{%0, %1, %2, %3, %4, %5, %6, %7, %8, %9, %10, %11, %12, %13, %14, %15, "
        "%16, %17, %18, %19, %20, %21, %22, %23, %24, %25, %26, %27, %28, %29, %30, %31, "
        "%32, %33, %34, %35, %36, %37, %38, %39, %40, %41, %42, %43, %44, %45, %46, %47, "
        "%48, %49, %50, %51, %52, %53, %54, %55, %56, %57, %58, %59, %60, %61, %62, %63}, "
        "da, db, p, 1, 1, 0, %67;\n}\n"
        : "+f"(d[0]), "+f"(d[1]), "+f"(d[2]), "+f"(d[3]), "+f"(d[4]), "+f"(d[5]), "+f"(d[6]), "+f"(d[7]),
          "+f"(d[8]), "+f"(d[9]), "+f"(d[10]), "+f"(d[11]), "+f"(d[12]), "+f"(d[13]), "+f"(d[14]), "+f"(d[15]),
          "+f"(d[16]), "+f"(d[17]), "+f"(d[18]), "+f"(d[19]), "+f"(d[20]), "+f"(d[21]), "+f"(d[22]), "+f"(d[23]),
          "+f"(d[24]), "+f"(d[25]), "+f"(d[26]), "+f"(d[27]), "+f"(d[28]), "+f"(d[29]), "+f"(d[30]), "+f"(d[31]),
          "+f"(e[0]), "+f"(e[1]), "+f"(e[2]), "+f"(e[3]), "+f"(e[4]), "+f"(e[5]), "+f"(e[6]), "+f"(e[7]),
          "+f"(e[8]), "+f"(e[9]), "+f"(e[10]), "+f"(e[11]), "+f"(e[12]), "+f"(e[13]), "+f"(e[14]), "+f"(e[15]),
          "+f"(e[16]), "+f"(e[17]), "+f"(e[18]), "+f"(e[19]), "+f"(e[20]), "+f"(e[21]), "+f"(e[22]), "+f"(e[23]),
          "+f"(e[24]), "+f"(e[25]), "+f"(e[26]), "+f"(e[27]), "+f"(e[28]), "+f"(e[29]), "+f"(e[30]), "+f"(e[31])
        : "r"(alo), "r"(blo), "r"(scale_d), "n"(TB), "n"(AHI), "n"(BHI));
}

template <int TB, uint32_t AHI, uint32_t BHI>
__device__ __forceinline__ void wgmma_n136(float (&d)[68], uint32_t alo, uint32_t blo, int scale_d) {
    asm volatile(
        "{\n.reg .pred p;\n.reg .b64 da, db;\n"
        "setp.ne.b32 p, %70, 0;\nmov.b64 da, {%68, %72};\nmov.b64 db, {%69, %73};\n"
        "wgmma.mma_async.sync.aligned.m64n136k16.f32.bf16.bf16 "
        "{%0, %1, %2, %3, %4, %5, %6, %7, %8, %9, %10, %11, %12, %13, %14, %15, "
        "%16, %17, %18, %19, %20, %21, %22, %23, %24, %25, %26, %27, %28, %29, %30, %31, "
        "%32, %33, %34, %35, %36, %37, %38, %39, %40, %41, %42, %43, %44, %45, %46, %47, "
        "%48, %49, %50, %51, %52, %53, %54, %55, %56, %57, %58, %59, %60, %61, %62, %63, "
        "%64, %65, %66, %67}, "
        "da, db, p, 1, 1, 0, %71;\n}\n"
        : "+f"(d[0]), "+f"(d[1]), "+f"(d[2]), "+f"(d[3]), "+f"(d[4]), "+f"(d[5]), "+f"(d[6]), "+f"(d[7]),
          "+f"(d[8]), "+f"(d[9]), "+f"(d[10]), "+f"(d[11]), "+f"(d[12]), "+f"(d[13]), "+f"(d[14]), "+f"(d[15]),
          "+f"(d[16]), "+f"(d[17]), "+f"(d[18]), "+f"(d[19]), "+f"(d[20]), "+f"(d[21]), "+f"(d[22]), "+f"(d[23]),
          "+f"(d[24]), "+f"(d[25]), "+f"(d[26]), "+f"(d[27]), "+f"(d[28]), "+f"(d[29]), "+f"(d[30]), "+f"(d[31]),
          "+f"(d[32]), "+f"(d[33]), "+f"(d[34]), "+f"(d[35]), "+f"(d[36]), "+f"(d[37]), "+f"(d[38]), "+f"(d[39]),
          "+f"(d[40]), "+f"(d[41]), "+f"(d[42]), "+f"(d[43]), "+f"(d[44]), "+f"(d[45]), "+f"(d[46]), "+f"(d[47]),
          "+f"(d[48]), "+f"(d[49]), "+f"(d[50]), "+f"(d[51]), "+f"(d[52]), "+f"(d[53]), "+f"(d[54]), "+f"(d[55]),
          "+f"(d[56]), "+f"(d[57]), "+f"(d[58]), "+f"(d[59]), "+f"(d[60]), "+f"(d[61]), "+f"(d[62]), "+f"(d[63]),
          "+f"(d[64]), "+f"(d[65]), "+f"(d[66]), "+f"(d[67])
        : "r"(alo), "r"(blo), "r"(scale_d), "n"(TB), "n"(AHI), "n"(BHI));
}

template <int TB, uint32_t AHI, uint32_t BHI>
__device__ __forceinline__ void wgmma_n176(float (&d)[88], uint32_t alo, uint32_t blo, int scale_d) {
    asm volatile(
        "{\n.reg .pred p;\n.reg .b64 da, db;\n"
        "setp.ne.b32 p, %90, 0;\nmov.b64 da, {%88, %92};\nmov.b64 db, {%89, %93};\n"
        "wgmma.mma_async.sync.aligned.m64n176k16.f32.bf16.bf16 "
        "{%0, %1, %2, %3, %4, %5, %6, %7, %8, %9, %10, %11, %12, %13, %14, %15, "
        "%16, %17, %18, %19, %20, %21, %22, %23, %24, %25, %26, %27, %28, %29, %30, %31, "
        "%32, %33, %34, %35, %36, %37, %38, %39, %40, %41, %42, %43, %44, %45, %46, %47, "
        "%48, %49, %50, %51, %52, %53, %54, %55, %56, %57, %58, %59, %60, %61, %62, %63, "
        "%64, %65, %66, %67, %68, %69, %70, %71, %72, %73, %74, %75, %76, %77, %78, %79, "
        "%80, %81, %82, %83, %84, %85, %86, %87}, "
        "da, db, p, 1, 1, 0, %91;\n}\n"
        : "+f"(d[0]), "+f"(d[1]), "+f"(d[2]), "+f"(d[3]), "+f"(d[4]), "+f"(d[5]), "+f"(d[6]), "+f"(d[7]),
          "+f"(d[8]), "+f"(d[9]), "+f"(d[10]), "+f"(d[11]), "+f"(d[12]), "+f"(d[13]), "+f"(d[14]), "+f"(d[15]),
          "+f"(d[16]), "+f"(d[17]), "+f"(d[18]), "+f"(d[19]), "+f"(d[20]), "+f"(d[21]), "+f"(d[22]), "+f"(d[23]),
          "+f"(d[24]), "+f"(d[25]), "+f"(d[26]), "+f"(d[27]), "+f"(d[28]), "+f"(d[29]), "+f"(d[30]), "+f"(d[31]),
          "+f"(d[32]), "+f"(d[33]), "+f"(d[34]), "+f"(d[35]), "+f"(d[36]), "+f"(d[37]), "+f"(d[38]), "+f"(d[39]),
          "+f"(d[40]), "+f"(d[41]), "+f"(d[42]), "+f"(d[43]), "+f"(d[44]), "+f"(d[45]), "+f"(d[46]), "+f"(d[47]),
          "+f"(d[48]), "+f"(d[49]), "+f"(d[50]), "+f"(d[51]), "+f"(d[52]), "+f"(d[53]), "+f"(d[54]), "+f"(d[55]),
          "+f"(d[56]), "+f"(d[57]), "+f"(d[58]), "+f"(d[59]), "+f"(d[60]), "+f"(d[61]), "+f"(d[62]), "+f"(d[63]),
          "+f"(d[64]), "+f"(d[65]), "+f"(d[66]), "+f"(d[67]), "+f"(d[68]), "+f"(d[69]), "+f"(d[70]), "+f"(d[71]),
          "+f"(d[72]), "+f"(d[73]), "+f"(d[74]), "+f"(d[75]), "+f"(d[76]), "+f"(d[77]), "+f"(d[78]), "+f"(d[79]),
          "+f"(d[80]), "+f"(d[81]), "+f"(d[82]), "+f"(d[83]), "+f"(d[84]), "+f"(d[85]), "+f"(d[86]), "+f"(d[87])
        : "r"(alo), "r"(blo), "r"(scale_d), "n"(TB), "n"(AHI), "n"(BHI));
}

template <int TB, uint32_t AHI, uint32_t BHI>
__device__ __forceinline__ void wgmma_n256(float (&d)[32], float (&e)[32], float (&f)[64], uint32_t alo, uint32_t blo, int scale_d) {
    asm volatile(
        "{\n.reg .pred p;\n.reg .b64 da, db;\n"
        "setp.ne.b32 p, %130, 0;\nmov.b64 da, {%128, %132};\nmov.b64 db, {%129, %133};\n"
        "wgmma.mma_async.sync.aligned.m64n256k16.f32.bf16.bf16 "
        "{%0, %1, %2, %3, %4, %5, %6, %7, %8, %9, %10, %11, %12, %13, %14, %15, "
        "%16, %17, %18, %19, %20, %21, %22, %23, %24, %25, %26, %27, %28, %29, %30, %31, "
        "%32, %33, %34, %35, %36, %37, %38, %39, %40, %41, %42, %43, %44, %45, %46, %47, "
        "%48, %49, %50, %51, %52, %53, %54, %55, %56, %57, %58, %59, %60, %61, %62, %63, "
        "%64, %65, %66, %67, %68, %69, %70, %71, %72, %73, %74, %75, %76, %77, %78, %79, "
        "%80, %81, %82, %83, %84, %85, %86, %87, %88, %89, %90, %91, %92, %93, %94, %95, "
        "%96, %97, %98, %99, %100, %101, %102, %103, %104, %105, %106, %107, %108, %109, %110, %111, "
        "%112, %113, %114, %115, %116, %117, %118, %119, %120, %121, %122, %123, %124, %125, %126, %127}, "
        "da, db, p, 1, 1, 0, %131;\n}\n"
        : "+f"(d[0]), "+f"(d[1]), "+f"(d[2]), "+f"(d[3]), "+f"(d[4]), "+f"(d[5]), "+f"(d[6]), "+f"(d[7]),
          "+f"(d[8]), "+f"(d[9]), "+f"(d[10]), "+f"(d[11]), "+f"(d[12]), "+f"(d[13]), "+f"(d[14]), "+f"(d[15]),
          "+f"(d[16]), "+f"(d[17]), "+f"(d[18]), "+f"(d[19]), "+f"(d[20]), "+f"(d[21]), "+f"(d[22]), "+f"(d[23]),
          "+f"(d[24]), "+f"(d[25]), "+f"(d[26]), "+f"(d[27]), "+f"(d[28]), "+f"(d[29]), "+f"(d[30]), "+f"(d[31]),
          "+f"(e[0]), "+f"(e[1]), "+f"(e[2]), "+f"(e[3]), "+f"(e[4]), "+f"(e[5]), "+f"(e[6]), "+f"(e[7]),
          "+f"(e[8]), "+f"(e[9]), "+f"(e[10]), "+f"(e[11]), "+f"(e[12]), "+f"(e[13]), "+f"(e[14]), "+f"(e[15]),
          "+f"(e[16]), "+f"(e[17]), "+f"(e[18]), "+f"(e[19]), "+f"(e[20]), "+f"(e[21]), "+f"(e[22]), "+f"(e[23]),
          "+f"(e[24]), "+f"(e[25]), "+f"(e[26]), "+f"(e[27]), "+f"(e[28]), "+f"(e[29]), "+f"(e[30]), "+f"(e[31]),
          "+f"(f[0]), "+f"(f[1]), "+f"(f[2]), "+f"(f[3]), "+f"(f[4]), "+f"(f[5]), "+f"(f[6]), "+f"(f[7]),
          "+f"(f[8]), "+f"(f[9]), "+f"(f[10]), "+f"(f[11]), "+f"(f[12]), "+f"(f[13]), "+f"(f[14]), "+f"(f[15]),
          "+f"(f[16]), "+f"(f[17]), "+f"(f[18]), "+f"(f[19]), "+f"(f[20]), "+f"(f[21]), "+f"(f[22]), "+f"(f[23]),
          "+f"(f[24]), "+f"(f[25]), "+f"(f[26]), "+f"(f[27]), "+f"(f[28]), "+f"(f[29]), "+f"(f[30]), "+f"(f[31]),
          "+f"(f[32]), "+f"(f[33]), "+f"(f[34]), "+f"(f[35]), "+f"(f[36]), "+f"(f[37]), "+f"(f[38]), "+f"(f[39]),
          "+f"(f[40]), "+f"(f[41]), "+f"(f[42]), "+f"(f[43]), "+f"(f[44]), "+f"(f[45]), "+f"(f[46]), "+f"(f[47]),
          "+f"(f[48]), "+f"(f[49]), "+f"(f[50]), "+f"(f[51]), "+f"(f[52]), "+f"(f[53]), "+f"(f[54]), "+f"(f[55]),
          "+f"(f[56]), "+f"(f[57]), "+f"(f[58]), "+f"(f[59]), "+f"(f[60]), "+f"(f[61]), "+f"(f[62]), "+f"(f[63])
        : "r"(alo), "r"(blo), "r"(scale_d), "n"(TB), "n"(AHI), "n"(BHI));
}

template <int MAP>
__global__ void __cluster_dims__(2, 1, 1) __launch_bounds__(384, 1) fused_kernel(const __grid_constant__ Params p) {
    extern __shared__ uint8_t smem_raw[];
    const uint32_t base = (smem_u32(smem_raw) + 1023u) & ~1023u;
    const uint32_t bars = base + OFF_BAR;
    auto bar = [&](int i) { return bars + 8u * i; };
    const int warp = threadIdx.x >> 5, lane = threadIdx.x & 31;
    int role = blockIdx.x >> 1;
    if (MAP == 1) {
        const int c = role;
        const int g = c < 4 ? 0 : c < 36 ? (c - 4) & 7 : 1 + (c - 36) % 7;
        const int r = c < 4 ? 4 + c : c < 36 ? (c - 4) >> 3 : 4 + (c - 36) / 7;
        role = ((g & 1) * 8 + r) * 4 + (g >> 1);
    }
    const int bid = role * 2 + (blockIdx.x & 1);
    const int nh = bid & 1, kq = (bid >> 1) & 3, t = bid >> 3, j = bid & 7;
    const int kh = kq & 1, km = kq >> 1;
    const CUtensorMap* th = (j & 4) ? &p.hi : &p.hr;
    auto x_bar = [&](int f) { return bar(f < 6 ? BAR_FULL_A + f : BAR_FULL_X + f - 6); };
    auto x_fill = [&](int f) {
        mbar_expect_tx(x_bar(f), A_BYTES);
        tma_load_2d(base + f * A_BYTES, &p.x, 64 * f, 128 * t, x_bar(f));
    };
    auto p1_fill = [&](int f) {
        const uint32_t dst = base + OFF_P + (f & 3) * P_BYTES, fb = bar(BAR_FULL_P + (f & 3));
        const int kk = f & 7;
        if (f < 8) {
            mbar_expect_tx(fb, 16384 + 128);
            tma_load_2d(dst, th, 64 * kk, 128 * (j & 3), fb);
            tma_load_2d(dst + 16384, &p.gw, 64 * kk, 0, fb);
        } else {
            mbar_expect_tx(fb, 24576);
            for (int q = 0; q < 3; q++) tma_load_2d(dst + q * 8192, &p.w1, HSL * j + 64 * q, 64 * kk, fb);
        }
    };
    if (threadIdx.x == 0) {
        mbar_init(bar(BAR_FULL_A), 1); mbar_init(bar(BAR_FULL_P), 1);
        x_fill(0); p1_fill(0);
    } else if (threadIdx.x == 32) {
        for (int i = 1; i < NA; i++) mbar_init(bar(BAR_FULL_A + i), 1);
        mbar_init(bar(BAR_FULL_X), 1); mbar_init(bar(BAR_FULL_X + 1), 1);
        for (int i = 1; i < 4; i++) mbar_init(bar(BAR_FULL_P + i), 1);
        for (int i = 0; i < NA; i++) mbar_init(bar(BAR_EMPTY_A + i), 8);
        for (int i = 0; i < 4; i++) {
            mbar_init(bar(BAR_EMPTY_P + i), 8);
            mbar_init(bar(BAR_FULL_B + i), 1); mbar_init(bar(BAR_EMPTY_B + i), 8);
        }
        prefetch_tmap(&p.w1);
    } else if (threadIdx.x == 64) {
        mbar_init(bar(BAR_SIG_AB), 8); mbar_init(bar(BAR_SIG_H), 8); mbar_init(bar(BAR_H_READY), 1);
        for (int i = 0; i < 8; i++) mbar_init(bar(BAR_AB_T + i), 1);
        mbar_init(bar(BAR_EPOCH), 1); mbar_init(bar(BAR_B0), 1);
    }
    __syncthreads();
    if (warp < 4) {
        asm volatile("setmaxnreg.dec.sync.aligned.u32 40;");
        if (warp == 0 && lane == 0) {
            x_fill(1); p1_fill(1); x_fill(2); p1_fill(2); x_fill(3); p1_fill(3);
#pragma unroll 1
            for (int f = 4; f < 8; f++) x_fill(f);
            const CUtensorMap* tc = km ? &p.ci : &p.cr;
            int slot = 0; uint32_t ph = 0;
#pragma unroll 1
            for (int i = 0; i < 27; i++) {
                const uint32_t dst = base + slot * A_BYTES, fb = bar(BAR_FULL_A + slot);
                if (i == DEFER_A) mbar_wait(bar(BAR_B0), 0);
                mbar_wait(bar(BAR_EMPTY_A + slot), ph);
                if (i < 16) {
                    mbar_expect_tx(fb, A_BYTES);
                    tma_load_2d(dst, tc, kh * 1024 + 64 * i, 128 * t, fb);
                } else {
                    if (i == 16) { mbar_wait(bar(BAR_H_READY), 0); fence_proxy_async_global(); }
                    const uint32_t bytes = i < 26 ? A_BYTES : 12288u;
                    mbar_expect_tx(fb, bytes);
                    bulk_load(dst, g_h + (size_t)(t * FG + kh * 86 + 8 * (i - 16)) * 128, bytes, fb);
                }
                if (++slot == NA) { slot = 0; ph ^= 1; }
            }
        } else if (warp == 1 && lane == 0) {
#pragma unroll 1
            for (int f = 4; f < 16; f++) {
                mbar_wait(bar(BAR_EMPTY_P + (f & 3)), ((f >> 2) & 1) ^ 1);
                p1_fill(f);
            }
#pragma unroll 1
            for (int f = 0; f < 22; f++) {
                const int bs = f & 3;
                const uint32_t dst = base + off_b(bs), fb = bar(BAR_FULL_B + bs);
                mbar_wait(bar(BAR_EMPTY_B + bs), (f >> 2) & 1);
                if (f < 16) {
                    if (!(f & 1)) { mbar_wait(bar(BAR_AB_T + (f >> 1)), 0); fence_proxy_async_global(); }
                    mbar_expect_tx(fb, B_BYTES);
                    const uint4* src = g_ab + (size_t)((km * 32 + kh * 16 + f) * 8 + nh * 4) * 512;
                    bulk_load(dst, src + km * 1024, 16384, fb);
                    bulk_load(dst + 16384, src + (km ^ 1) * 1024, 16384, fb);
                    if (f == 0) mbar_arrive(bar(BAR_B0));
                } else {
                    const int nsub = f < 21 ? 2 : 1;
                    mbar_expect_tx(fb, nsub * 16384);
                    for (int s = 0; s < nsub; s++)
                        for (int q = 0; q < 2; q++)
                            tma_load_2d(dst + s * 16384 + q * 8192, &p.w2, nh * 256 + km * 128 + q * 64, kh * 688 + 128 * (f - 16) + 64 * s, fb);
                }
            }
        } else if (warp == 2 && lane == 0) {
            const uint32_t ep = g_epoch[bid] + 1;
            g_epoch[bid] = ep;
            asm volatile("st.shared.u32 [%0], %1;" ::"r"(base + OFF_EPOCH), "r"(ep) : "memory");
            mbar_arrive(bar(BAR_EPOCH));
            prefetch_tmap(km ? &p.ci : &p.cr);
            prefetch_tmap(&p.w2);
            mbar_wait(bar(BAR_SIG_AB), 0);
            fence_proxy_async_global();
            red_release_add(&g_cnt_ab[((j >> 1) * 16 + t) * 32], 1);
            mbar_wait(bar(BAR_SIG_H), 0);
            fence_proxy_async_global();
            red_release_add(&g_cnt_h[t * 32], 1);
            wait_counter(&g_cnt_h[t * 32], 8 * ep);
            mbar_arrive(bar(BAR_H_READY));
        } else if (warp == 3) {
            const long long t0 = clock64();
            while (clock64() - t0 < 800) {}
            if (lane == 0 && t < 4) l2_prefetch_tile(th, 64 * (4 + t), 128 * (j & 3));
            mbar_wait(x_bar(6), 0);
            if (lane == 0) l2_prefetch((const uint8_t*)p.pw1 + bid * 11008, 11008);
            mbar_wait(bar(BAR_EPOCH), 0);
            uint32_t ep;
            asm volatile("ld.shared.u32 %0, [%1];" : "=r"(ep) : "r"(base + OFF_EPOCH) : "memory");
            const uint32_t* cnt = &g_cnt_ab[((km * 2 + nh) * 16 + kh * 8 + (lane & 7)) * 32];
            bool done = lane >= 8 || (int32_t)(ld_acquire(cnt) - 2 * ep) >= 0;
            if (done && lane < 8) mbar_arrive(bar(BAR_AB_T + lane));
            mbar_wait(bar(BAR_EMPTY_A + POLL_AT), 0);
            for (uint32_t n = 0; n < SPIN_LIMIT && !__all_sync(0xffffffffu, done); n++) {
                if (!done && (int32_t)(ld_acquire(cnt) - 2 * ep) >= 0) {
                    mbar_arrive(bar(BAR_AB_T + lane));
                    done = true;
                }
                __nanosleep(POLL_NS);
            }
            mbar_wait(bar(BAR_SIG_H), 0);
            if (lane == 0) l2_prefetch((const uint8_t*)p.pw2 + bid * 11008, 11008);
        }
    } else {
        asm volatile("setmaxnreg.inc.sync.aligned.u32 232;");
        const int w = __shfl_sync(0xffffffffu, (warp - 4) >> 2, 0), q = warp & 3, ctid = threadIdx.x - 128;
        constexpr uint32_t H_K128 = desc_hi(1024, 1);
        constexpr uint32_t H_MN128 = desc_hi(1024, 1);
        constexpr uint32_t H_AB = desc_hi(1024, 0);
        constexpr uint32_t H_H = desc_hi(128, 0);
        const uint32_t d0 = (base & 0x3FFFFu) >> 4;
        auto release = [&](int b) { if (lane == 0) mbar_arrive(bar(b)); };
        float g0, g1, o0, o1;
        float cO[32], cS[32], cX[64];
        uint32_t hpk[44];
        {
            float accAB[68], accH[88];
            float zz0 = 0.f, zz1 = 0.f;
            uint32_t* abdst = (uint32_t*)(g_ab + (size_t)(((j >> 2) * 32 + 2 * t + w) * 8 + (j & 3) * 2) * 512) + (2 * q) * 32 + lane;
            uint32_t abpk[32];
            const bool fast = (t & 7) < AB_FAST_TILES;
            auto ab_store = [&](int slotno) {
#pragma unroll
                for (int e = 0; e < 32; e++) {
                    const bool inf = e * (4 * AB_FAST_STEPS + AB_PRE) / 32 == slotno, ins = e * (4 * AB_SLOW_STEPS + AB_PRE) / 32 == slotno;
                    if ((inf && ins) || (inf && fast) || (ins && !fast)) abdst[(e >> 1) * 256 + (e & 1) * 32] = abpk[e];
                }
            };
#pragma unroll
            for (int s = 0; s < 16; s++) {
                const int kk = s & 7;
                const bool isab = s < 8;
                if (isab) mbar_wait(x_bar(kk), 0);
                mbar_wait(bar(BAR_FULL_P + (s & 3)), (s >> 2) & 1);
                wg_fence();
#pragma unroll
                for (int i = 0; i < 4; i++) {
                    const uint32_t da = d0 + w * 512 + desc_off(kk * A_BYTES + i * 32, 16);
                    if (isab) wgmma_n136<0, H_K128, H_K128>(accAB, da, d0 + desc_off(OFF_P + (s & 3) * P_BYTES + i * 32, 16), (kk | i) != 0);
                    else wgmma_n176<1, H_K128, H_MN128>(accH, da, d0 + desc_off(OFF_P + (s & 3) * P_BYTES + i * 2048, 8192), (kk | i) != 0);
                    if (s >= 9 && s < 9 + AB_SLOW_STEPS) ab_store(AB_PRE + (s - (9)) * 4 + i);
                }
                wg_commit();
                if (s > 0) {
                    wg_wait<1>();
                    if (s - 1 < 12) release(BAR_EMPTY_P + ((s - 1) & 3));
                    if (s - 1 >= 13) release(BAR_EMPTY_B + (s - 1) - 13);
                    if (s - 1 >= 8 && s - 1 < 14) release(BAR_EMPTY_A + s - 9);
                }
                if ((s == 8 + AB_FAST_STEPS && fast) || (s == 8 + AB_SLOW_STEPS && !fast)) { __syncwarp(); release(BAR_SIG_AB); }
                if (s == 8) {
                    reg_fence(accAB);
#pragma unroll
                    for (int e = 0; e < 32; e++) abpk[e] = pack_bf16(accAB[2 * e], accAB[2 * e + 1]);
                    zz0 = accAB[64]; zz1 = accAB[66];
                    reg_fence(abpk);
                    asm volatile("" : "+f"(zz0), "+f"(zz1)::"memory");
#pragma unroll
                    for (int u = 0; u < AB_PRE; u++) ab_store(u);
                }
            }
            wg_wait<0>();
            release(BAR_EMPTY_B + 2);
            release(BAR_EMPTY_B + 3);
            reg_fence(accH);
#pragma unroll
            for (int i = 0; i < 22; i++) {
                hpk[2 * i] = pack_bf16_relu(accH[4 * i], accH[4 * i + 1]);
                hpk[2 * i + 1] = pack_bf16_relu(accH[4 * i + 2], accH[4 * i + 3]);
            }
            reg_fence(hpk);
            const float z0 = round_bf16(__shfl_sync(0xffffffffu, zz0, lane & ~3));
            const float z1 = round_bf16(__shfl_sync(0xffffffffu, zz1, lane & ~3));
            g0 = round_bf16(__fdividef(1.f, 1.f + __expf(-z0)));
            g1 = round_bf16(__fdividef(1.f, 1.f + __expf(-z1)));
            o0 = round_bf16(1.f - g0); o1 = round_bf16(1.f - g1);
        }
        int sA = 0; uint32_t phA = 1;
        int pA = 0;
        mbar_wait(bar(BAR_EPOCH), 0);
        uint32_t tag;
        asm volatile("ld.shared.u32 %0, [%1];" : "=r"(tag) : "r"(base + OFF_EPOCH) : "memory");
        tag = (tag & 1u) << 16;
        uint4* pdst = g_part + (size_t)(bid ^ 4) * 2048 + ctid;
        uint4* pre = pdst;
        uint4* orow = (uint4*)(p.pout + (size_t)(128 * t + 64 * w + 16 * q + (lane >> 3)) * DM + nh * 256 + kq * 64) + (lane & 7);
        uint32_t* hdst = (uint32_t*)(g_h + (size_t)(t * FG + 22 * j) * 128) + (8 * w + 2 * q) * 32 + lane;
        auto c_step = [&](int i, bool trickle) {
            const uint32_t da = d0 + w * 512 + sA * (A_BYTES >> 4) + desc_off(0, 16), db = d0 + (off_b(i & 3) >> 4) + desc_off(0, 128);
            mbar_wait(bar(BAR_FULL_A + sA), phA);
            mbar_wait(bar(BAR_FULL_B + (i & 3)), (i >> 2) & 1);
            wg_fence();
#pragma unroll
            for (int u = 0; u < 4; u++) {
                wgmma_n256<1, H_K128, H_AB>(cO, cS, cX, da + u * 2, db + u * 16, (i | u) != 0);
                if (trickle) {
#pragma unroll
                    for (int e = 0; e < 44; e++)
                        if (e * (4 * H_STEPS) / 44 == (i - H_START) * 4 + u) hdst[(e >> 1) * 512 + (e & 1) * 32] = hpk[e];
                }
            }
            wg_commit();
            if (i > 0) {
                wg_wait<1>();
                release(BAR_EMPTY_B + ((i - 1) & 3));
                release(BAR_EMPTY_A + pA);
            }
            if (trickle && i >= ZERO_STEP && i < ZERO_STEP + 4) orow[(i - ZERO_STEP) * 4 * (DM / 8)] = make_uint4(0u, 0u, 0u, 0u);
            if (trickle && i == H_START + H_STEPS - 1) { __syncwarp(); release(BAR_SIG_H); }
            if (!trickle && i < H_START + H_STEPS + 4) {
                st_relaxed_v4(pre, tag ^ TAG_BIT, tag ^ TAG_BIT, tag ^ TAG_BIT, tag ^ TAG_BIT);
                st_relaxed_v4(pre + 256, tag ^ TAG_BIT, tag ^ TAG_BIT, tag ^ TAG_BIT, tag ^ TAG_BIT);
                pre += 512;
            }
            pA = sA;
            if (++sA == NA) { sA = 0; phA ^= 1; }
        };
#pragma unroll
        for (int i = 0; i < H_START + H_STEPS; i++) c_step(i, true);
#pragma unroll 1
        for (int i = H_START + H_STEPS; i < 16; i++) c_step(i, false);
        static_assert(H_START + H_STEPS + 4 <= 16 && ZERO_STEP + 4 <= H_START + H_STEPS, "");
        float hO[32], hS[32];
        uint32_t xpk[32];
        uint4 rs[4], ro[4];
        const uint4* psrc = g_part + (size_t)bid * 2048 + ctid;
        const float k0 = km ? -g0 : g0, k1 = km ? -g1 : g1;
        auto p_io = [&](int slotno) {
#pragma unroll
            for (int o = 0; o < 8; o++) {
                const int e = o ^ 4;
                if (o * X_SLOTS / 8 == slotno) st_relaxed_v4(pdst + e * 256, xpk[4 * e], xpk[4 * e + 1], xpk[4 * e + 2], xpk[4 * e + 3]);
                if (o < 4 && o * X_SLOTS / 8 + X_DELAY == slotno) rs[o] = ld_relaxed_v4(psrc + e * 256);
                if (o >= 4 && X_LOAD2 + 2 * (o - 4) == slotno) ro[o - 4] = ld_relaxed_v4(psrc + e * 256);
            }
        };
        auto fold4 = [&](float (&c)[32], int v, const uint4 (&r)[4]) {
            const uint32_t wa = (v & 1) ? r[v >> 1].z : r[v >> 1].x, wb = (v & 1) ? r[v >> 1].w : r[v >> 1].y;
            c[4 * v + 0] = k0 * (c[4 * v + 0] - lo_f(wa)); c[4 * v + 1] = k0 * (c[4 * v + 1] - hi_f(wa));
            c[4 * v + 2] = k1 * (c[4 * v + 2] - lo_f(wb)); c[4 * v + 3] = k1 * (c[4 * v + 3] - hi_f(wb));
#pragma unroll
            for (int u = 0; u < 4; u++) asm volatile("" : "+f"(c[4 * v + u])::"memory");
        };
        static_assert(3 * X_SLOTS / 8 + X_DELAY <= 32 && X_LOAD2 > 32 && X_LOAD2 + 6 <= 39, "");
#pragma unroll
        for (int i = 0; i < 11; i++) {
            const int fb = i >> 1;
            const uint32_t da = d0 + w * 64 + sA * (A_BYTES >> 4) + desc_off(0, 2048), db = d0 + desc_off(off_b(fb & 3) + (i & 1) * 16384, 8192);
            mbar_wait(bar(BAR_FULL_A + sA), phA);
            if (!(i & 1)) mbar_wait(bar(BAR_FULL_B + (fb & 3)), (fb >> 2) & 1);
            wg_fence();
#pragma unroll
            for (int u = 0; u < (i < 10 ? 4 : 3); u++) {
                wgmma_n128<1, H_H, H_MN128>(hO, hS, da + u * 256, db + u * 128, (i | u) != 0);
                if (i > 0) p_io(1 + (i - 1) * 4 + u);
                if (i >= 9) fold4(cS, (i - 9) * 4 + u, rs);
            }
            wg_commit();
            wg_wait<1>();
            if (i < 10) {
                release(BAR_EMPTY_A + pA);
                if (!(i & 1)) release(BAR_EMPTY_B + ((fb - 1) & 3));
            }
            if (i == 8) recv_tagged(rs, psrc + 4 * 256, tag);
            if (i == 0) {
                reg_fence(cO); reg_fence(cS); reg_fence(cX);
#pragma unroll
                for (int e = 0; e < 32; e++) xpk[e] = (pack_bf16(cX[2 * e], cX[2 * e + 1]) & ~TAG_BIT) | tag;
                reg_fence(xpk);
                p_io(0);
            }
            pA = sA;
            if (++sA == NA) { sA = 0; phA ^= 1; }
        }
        fold4(cS, 7, rs);
        recv_tagged(ro, psrc, tag);
#pragma unroll
        for (int v = 0; v < 8; v++) fold4(cO, v, ro);
        mbar_wait(bar(BAR_H_READY), 0);
        mbar_wait(bar(BAR_EMPTY_B + 2), 1);
        wg_wait<0>();
        reg_fence(hO); reg_fence(hS);
        {
            const uint32_t stg = base + off_b(2) + (warp - 4) * 4096;
            const int row = ((lane >> 3) & 1) * 8 + (lane & 7);
#pragma unroll
            for (int hf = 0; hf < 2; hf++) {
                float (&c)[32] = hf ? cS : cO;
                float (&h)[32] = hf ? hS : hO;
#pragma unroll
                for (int u = 0; u < 4; u++) {
                    uint32_t v[4];
#pragma unroll
                    for (int e = 0; e < 4; e++) {
                        const float o = (e & 1) ? o1 : o0;
                        v[e] = pack_bf16(fmaf(o, h[8 * u + 2 * e], c[8 * u + 2 * e]), fmaf(o, h[8 * u + 2 * e + 1], c[8 * u + 2 * e + 1]));
                    }
                    const int cc = 2 * u + (lane >> 4);
                    stmatrix_x4(stg + hf * 2048 + row * 128 + ((cc ^ (row & 7)) << 4), v[0], v[1], v[2], v[3]);
                }
                __syncwarp();
                uint4* dst = orow + (hf - kh) * 8;
#pragma unroll
                for (int u = 0; u < 4; u++) {
                    const int r = 4 * u + (lane >> 3);
                    const uint4 v = lds128(stg + hf * 2048 + r * 128 + (((lane & 7) ^ (r & 7)) << 4));
                    asm volatile("red.relaxed.gpu.global.add.noftz.v4.bf16x2 [%0], {%1, %2, %3, %4};"
                                 ::"l"(dst + u * 4 * (DM / 8)), "r"(v.x), "r"(v.y), "r"(v.z), "r"(v.w) : "memory");
                }
            }
        }
    }
}

__device__ __nv_bfloat16 g_fb[SEQ * (2 * DM + DFF)];
__global__ void fb_stage1(const __nv_bfloat16* x, const __nv_bfloat16* hr, const __nv_bfloat16* hi, const __nv_bfloat16* w1) {
    __shared__ float xs[DM];
    const int r = blockIdx.x;
    for (int d = threadIdx.x; d < DM; d += blockDim.x) xs[d] = __bfloat162float(x[r * DM + d]);
    __syncthreads();
    for (int c = threadIdx.x; c < 2 * DM + DFF; c += blockDim.x) {
        float s = 0.f;
        if (c < 2 * DM) {
            const __nv_bfloat16* m = (c < DM ? hr : hi) + (c & (DM - 1)) * DM;
            for (int d = 0; d < DM; d++) s += xs[d] * __bfloat162float(m[d]);
        } else {
            for (int d = 0; d < DM; d++) s += xs[d] * __bfloat162float(w1[d * DFF + c - 2 * DM]);
            s = fmaxf(s, 0.f);
        }
        g_fb[(size_t)r * (2 * DM + DFF) + c] = __float2bfloat16_rn(s);
    }
}
__global__ void fb_stage2(const __nv_bfloat16* x, const __nv_bfloat16* cr, const __nv_bfloat16* ci, const __nv_bfloat16* w2,
                          const __nv_bfloat16* gate, __nv_bfloat16* out) {
    const int r = blockIdx.x, c = threadIdx.x;
    float z = 0.f, y = 0.f, f = 0.f;
    for (int d = 0; d < DM; d++) z += __bfloat162float(x[r * DM + d]) * __bfloat162float(gate[d]);
    for (int s = 0; s < SEQ; s++) {
        const __nv_bfloat16* ab = g_fb + (size_t)s * (2 * DM + DFF);
        y += __bfloat162float(cr[(size_t)r * SEQ + s]) * __bfloat162float(ab[c]) - __bfloat162float(ci[(size_t)r * SEQ + s]) * __bfloat162float(ab[DM + c]);
    }
    for (int k = 0; k < DFF; k++) f += __bfloat162float(g_fb[(size_t)r * (2 * DM + DFF) + 2 * DM + k]) * __bfloat162float(w2[k * DM + c]);
    const float g = 1.f / (1.f + __expf(-z));
    out[r * DM + c] = __float2bfloat16_rn(g * y + (1.f - g) * f);
}
__global__ void probe_kernel() {}

typedef CUresult (*EncodeFn)(CUtensorMap*, CUtensorMapDataType, cuuint32_t, void*, const cuuint64_t*, const cuuint64_t*,
                             const cuuint32_t*, const cuuint32_t*, CUtensorMapInterleave, CUtensorMapSwizzle,
                             CUtensorMapL2promotion, CUtensorMapFloatOOBfill);

bool make_map(EncodeFn enc, CUtensorMap* m, const void* ptr, uint64_t inner, uint64_t outer, uint32_t box_inner, uint32_t box_outer) {
    cuuint64_t dims[2] = {inner, outer};
    cuuint64_t strides[1] = {inner * 2};
    cuuint32_t box[2] = {box_inner, box_outer};
    cuuint32_t es[2] = {1, 1};
    return enc(m, CU_TENSOR_MAP_DATA_TYPE_BFLOAT16, 2, const_cast<void*>(ptr), dims, strides, box, es, CU_TENSOR_MAP_INTERLEAVE_NONE,
               CU_TENSOR_MAP_SWIZZLE_128B, CU_TENSOR_MAP_L2_PROMOTION_L2_128B, CU_TENSOR_MAP_FLOAT_OOB_FILL_NONE) == CUDA_SUCCESS;
}

template <class K>
int max_clusters(K kernel, int cluster, bool set_dim) {
    cudaLaunchConfig_t cfg = {};
    cfg.gridDim = dim3(NCTA);
    cfg.blockDim = dim3(384);
    cfg.dynamicSmemBytes = SMEM_BYTES;
    cudaLaunchAttribute at[1];
    at[0].id = cudaLaunchAttributeClusterDimension;
    at[0].val.clusterDim.x = cluster;
    at[0].val.clusterDim.y = 1;
    at[0].val.clusterDim.z = 1;
    cfg.attrs = at;
    cfg.numAttrs = set_dim ? 1 : 0;
    int n = 0;
    if (cudaOccupancyMaxActiveClusters(&n, kernel, &cfg) != cudaSuccess) { (void)cudaGetLastError(); return 0; }
    return n;
}

}

extern "C" void kernel_launch(void* const* d_in, const int* in_sizes, int n_in, void* d_out, int out_size) {
    (void)in_sizes; (void)n_in; (void)out_size;
    static Params prm;
    static const void* cached[10] = {};
    static int mode = -1;
    bool same = mode >= 0 && cached[9] == d_out;
    for (int i = 0; i < 9; i++) same = same && cached[i] == d_in[i];
    if (!same) {
        prm.px = (const __nv_bfloat16*)d_in[0];
        prm.pcr = (const __nv_bfloat16*)d_in[1];
        prm.pci = (const __nv_bfloat16*)d_in[2];
        prm.phr = (const __nv_bfloat16*)d_in[3];
        prm.phi = (const __nv_bfloat16*)d_in[4];
        prm.pw1 = (const __nv_bfloat16*)d_in[6];
        prm.pw2 = (const __nv_bfloat16*)d_in[7];
        prm.gate = (const __nv_bfloat16*)d_in[8];
        prm.pout = (__nv_bfloat16*)d_out;
        void* fn = nullptr;
        cudaDriverEntryPointQueryResult qr;
        bool ok = cudaGetDriverEntryPoint("cuTensorMapEncodeTiled", &fn, cudaEnableDefault, &qr) == cudaSuccess && fn != nullptr;
        EncodeFn enc = (EncodeFn)fn;
        ok = ok && make_map(enc, &prm.x, prm.px, DM, SEQ, 64, 128) && make_map(enc, &prm.hr, prm.phr, DM, DM, 64, 128) &&
             make_map(enc, &prm.hi, prm.phi, DM, DM, 64, 128) && make_map(enc, &prm.w1, prm.pw1, DFF, DM, 64, 64) &&
             make_map(enc, &prm.cr, prm.pcr, SEQ, SEQ, 64, 128) && make_map(enc, &prm.ci, prm.pci, SEQ, SEQ, 64, 128) &&
             make_map(enc, &prm.w2, prm.pw2, DM, DFF, 64, 64) && make_map(enc, &prm.gw, prm.gate, DM, 1, 64, 1);
        ok = ok && cudaFuncSetAttribute(fused_kernel<0>, cudaFuncAttributeMaxDynamicSharedMemorySize, SMEM_BYTES) == cudaSuccess &&
             cudaFuncSetAttribute(fused_kernel<1>, cudaFuncAttributeMaxDynamicSharedMemorySize, SMEM_BYTES) == cudaSuccess &&
             cudaFuncSetAttribute(probe_kernel, cudaFuncAttributeMaxDynamicSharedMemorySize, SMEM_BYTES) == cudaSuccess;
        ok = ok && max_clusters(fused_kernel<0>, 2, false) >= NCTA / 2;
        (void)cudaGetLastError();
        mode = !ok ? 2 : (max_clusters(probe_kernel, 2, true) == 66 && max_clusters(probe_kernel, 4, true) == 30 && max_clusters(probe_kernel, 8, true) == 15) ? 1 : 0;
        for (int i = 0; i < 9; i++) cached[i] = d_in[i];
        cached[9] = d_out;
    }
    if (mode == 1) {
        fused_kernel<1><<<NCTA, 384, SMEM_BYTES>>>(prm);
    } else if (mode == 0) {
        fused_kernel<0><<<NCTA, 384, SMEM_BYTES>>>(prm);
    } else {
        fb_stage1<<<SEQ, 256>>>(prm.px, prm.phr, prm.phi, prm.pw1);
        fb_stage2<<<SEQ, DM>>>(prm.px, prm.pcr, prm.pci, prm.pw2, prm.gate, prm.pout);
    }
}
```

```cpp
#include <cuda_runtime.h>
#include <cuda.h>
#include <cuda_bf16.h>
#include <stdint.h>

namespace {

constexpr int SEQ = 2048, DM = 512, DFF = 1376;
constexpr int NCTA = 128;
constexpr int NA = 6;
constexpr uint32_t A_BYTES = 16384, B_BYTES = 32768, P_BYTES = 24576;
constexpr uint32_t OFF_P = 8 * A_BYTES;
constexpr uint32_t OFF_BAR = OFF_P + 4 * P_BYTES;
constexpr uint32_t OFF_EPOCH = OFF_BAR + 8 * 48;
constexpr uint32_t SMEM_BYTES = OFF_BAR + 512 + 1024;
__host__ __device__ constexpr uint32_t off_b(int s) { return s == 3 ? 6 * A_BYTES : OFF_P + s * B_BYTES; }
constexpr int HSL = 176;
constexpr int FG = 176;
constexpr uint32_t SPIN_LIMIT = 1u << 20;
constexpr uint32_t TAG_BIT = 0x10000u;

constexpr int BAR_FULL_A = 0, BAR_EMPTY_A = 6, BAR_FULL_X = 12, BAR_FULL_B = 14, BAR_EMPTY_B = 18, BAR_FULL_P = 22, BAR_EMPTY_P = 26;
constexpr int BAR_H_READY = 30, BAR_SIG_AB = 31, BAR_SIG_H = 32, BAR_EPOCH = 33, BAR_B0 = 34;
constexpr int BAR_AB_T = 40;

constexpr int AB_PRE = 2, AB_FAST_STEPS = 4, AB_SLOW_STEPS = 6, AB_FAST_TILES = 2;
constexpr int H_START = 1, H_STEPS = 8, ZERO_STEP = 2;
constexpr int X_SLOTS = 28, X_DELAY = 16, X_LOAD2 = 33;
constexpr int Z_STEP = 8;
constexpr int DEFER_A = 3, POLL_AT = 3, POLL_NS = 50, POLL_SLOW_NS = 200;

struct Params {
    CUtensorMap x, hr, hi, w1, cr, ci, w2, hr32, hi32;
    const __nv_bfloat16 *px, *phr, *phi, *pw1, *pcr, *pci, *pw2, *gate;
    __nv_bfloat16* pout;
};

__device__ uint4 g_ab[2 * 32 * 8 * 512];
__device__ uint4 g_h[16 * FG * 128];
__device__ uint4 g_part[NCTA * 8 * 256];
__device__ float g_z[SEQ];
__device__ uint32_t g_cnt_ab[32 * 32];
__device__ uint32_t g_cnt_h[16 * 32];
__device__ uint32_t g_epoch[NCTA];

__device__ __forceinline__ uint32_t smem_u32(const void* p) { return (uint32_t)__cvta_generic_to_shared(p); }
__device__ __forceinline__ void mbar_init(uint32_t bar, uint32_t cnt) {
    asm volatile("mbarrier.init.shared::cta.b64 [%0], %1;" ::"r"(bar), "r"(cnt) : "memory");
}
__device__ __forceinline__ void mbar_expect_tx(uint32_t bar, uint32_t bytes) {
    asm volatile("mbarrier.arrive.expect_tx.shared::cta.b64 _, [%0], %1;" ::"r"(bar), "r"(bytes) : "memory");
}
__device__ __forceinline__ void mbar_arrive(uint32_t bar) {
    asm volatile("mbarrier.arrive.shared::cta.b64 _, [%0];" ::"r"(bar) : "memory");
}
__device__ __forceinline__ void mbar_wait(uint32_t bar, uint32_t parity) {
    asm volatile(
        "{\n.reg .pred p;\n.reg .u32 n;\n"
        "mbarrier.try_wait.parity.shared::cta.b64 p, [%0], %1;\n"
        "@p bra LAB_DONE;\n"
        "mov.u32 n, 0;\n"
        "LAB_WAIT:\n"
        "mbarrier.try_wait.parity.shared::cta.b64 p, [%0], %1;\n"
        "@p bra LAB_DONE;\n"
        "add.u32 n, n, 1;\nsetp.lt.u32 p, n, %2;\n@p bra LAB_WAIT;\ntrap;\n"
        "LAB_DONE:\n}\n" ::"r"(bar), "r"(parity), "n"(SPIN_LIMIT) : "memory");
}
__device__ __forceinline__ void wait_counter(const uint32_t* p, uint32_t target) {
    asm volatile(
        "{\n.reg .pred p;\n.reg .u32 n;\n.reg .s32 v;\nmov.u32 n, 0;\n"
        "LAB_WAIT:\n"
        "ld.acquire.gpu.global.u32 v, [%0];\n"
        "sub.s32 v, v, %1;\nsetp.ge.s32 p, v, 0;\n"
        "@p bra LAB_DONE;\n"
        "add.u32 n, n, 1;\nsetp.lt.u32 p, n, %2;\n@p bra LAB_WAIT;\ntrap;\n"
        "LAB_DONE:\n}\n" ::"l"(p), "r"(target), "n"(SPIN_LIMIT) : "memory");
}
__device__ __forceinline__ void tma_load_2d(uint32_t dst, const CUtensorMap* tm, int c0, int c1, uint32_t bar) {
    asm volatile("cp.async.bulk.tensor.2d.shared::cluster.global.mbarrier::complete_tx::bytes [%0], [%1, {%3, %4}], [%2];"
                 ::"r"(dst), "l"(tm), "r"(bar), "r"(c0), "r"(c1) : "memory");
}
__device__ __forceinline__ void bulk_load(uint32_t dst, const void* src, uint32_t bytes, uint32_t bar) {
    asm volatile("cp.async.bulk.shared::cluster.global.mbarrier::complete_tx::bytes [%0], [%1], %2, [%3];"
                 ::"r"(dst), "l"(src), "r"(bytes), "r"(bar) : "memory");
}
__device__ __forceinline__ void l2_prefetch(const void* src, uint32_t bytes) {
    asm volatile("cp.async.bulk.prefetch.L2.global [%0], %1;" ::"l"(src), "r"(bytes) : "memory");
}
__device__ __forceinline__ void l2_prefetch_tile(const CUtensorMap* tm, int c0, int c1) {
    asm volatile("cp.async.bulk.prefetch.tensor.2d.L2.global [%0, {%1, %2}];" ::"l"(tm), "r"(c0), "r"(c1) : "memory");
}
__device__ __forceinline__ void prefetch_tmap(const CUtensorMap* tm) {
    asm volatile("prefetch.tensormap [%0];" ::"l"(tm) : "memory");
}
__device__ __forceinline__ void fence_proxy_async_global() { asm volatile("fence.proxy.async.global;" ::: "memory"); }
__device__ __forceinline__ void red_release_add(uint32_t* p, uint32_t v) {
    asm volatile("red.release.gpu.global.add.u32 [%0], %1;" ::"l"(p), "r"(v) : "memory");
}
__device__ __forceinline__ void red_relaxed_add(uint32_t* p, uint32_t v) {
    asm volatile("red.relaxed.gpu.global.add.u32 [%0], %1;" ::"l"(p), "r"(v) : "memory");
}
__device__ __forceinline__ uint32_t ld_acquire(const uint32_t* p) {
    uint32_t v;
    asm volatile("ld.acquire.gpu.global.u32 %0, [%1];" : "=r"(v) : "l"(p) : "memory");
    return v;
}
__device__ __forceinline__ void st_relaxed_v4(uint4* p, uint32_t a, uint32_t b, uint32_t c, uint32_t d) {
    asm volatile("st.relaxed.gpu.global.v4.b32 [%0], {%1, %2, %3, %4};" ::"l"(p), "r"(a), "r"(b), "r"(c), "r"(d) : "memory");
}
__device__ __forceinline__ uint4 ld_relaxed_v4(const uint4* p) {
    uint4 v;
    asm volatile("ld.relaxed.gpu.global.v4.b32 {%0, %1, %2, %3}, [%4];" : "=r"(v.x), "=r"(v.y), "=r"(v.z), "=r"(v.w) : "l"(p) : "memory");
    return v;
}
__device__ __forceinline__ uint4 ldg128(const uint4* p) {
    uint4 v;
    asm volatile("ld.global.nc.v4.u32 {%0, %1, %2, %3}, [%4];" : "=r"(v.x), "=r"(v.y), "=r"(v.z), "=r"(v.w) : "l"(p));
    return v;
}
__device__ __forceinline__ uint4 lds128(uint32_t addr) {
    uint4 v;
    asm volatile("ld.shared.v4.u32 {%0, %1, %2, %3}, [%4];" : "=r"(v.x), "=r"(v.y), "=r"(v.z), "=r"(v.w) : "r"(addr) : "memory");
    return v;
}
__device__ __forceinline__ void stmatrix_x4(uint32_t addr, uint32_t a, uint32_t b, uint32_t c, uint32_t d) {
    asm volatile("stmatrix.sync.aligned.m8n8.x4.shared.b16 [%0], {%1, %2, %3, %4};" ::"r"(addr), "r"(a), "r"(b), "r"(c), "r"(d) : "memory");
}
__device__ __forceinline__ uint32_t and3(uint32_t a, uint32_t b, uint32_t c) {
    uint32_t r;
    asm("lop3.b32 %0, %1, %2, %3, 0x80;" : "=r"(r) : "r"(a), "r"(b), "r"(c));
    return r;
}
__device__ __forceinline__ uint32_t eq3(uint32_t a, uint32_t b, uint32_t t) {
    uint32_t r;
    asm("lop3.b32 %0, %1, %2, %3, 0x81;" : "=r"(r) : "r"(a), "r"(b), "r"(t));
    return r;
}
__device__ __forceinline__ uint32_t fresh_bits(const uint4& v, uint32_t tag) { return eq3(v.x, v.y, tag) & eq3(v.z, v.w, tag); }
__device__ __forceinline__ void recv_tagged(uint4 (&rp)[4], const uint4* src, uint32_t tag) {
    uint32_t m = and3(fresh_bits(rp[0], tag), fresh_bits(rp[1], tag), fresh_bits(rp[2], tag) & fresh_bits(rp[3], tag));
    for (uint32_t n = 0; !(m & TAG_BIT) && n < SPIN_LIMIT; n++) {
#pragma unroll
        for (int u = 0; u < 4; u++) {
            if (!(fresh_bits(rp[u], tag) & TAG_BIT)) rp[u] = ld_relaxed_v4(src + u * 256);
        }
        m = and3(fresh_bits(rp[0], tag), fresh_bits(rp[1], tag), fresh_bits(rp[2], tag) & fresh_bits(rp[3], tag));
    }
    __syncwarp();
}
__device__ __forceinline__ float lo_f(uint32_t w) { return __uint_as_float(w << 16); }
__device__ __forceinline__ float hi_f(uint32_t w) { return __uint_as_float(w & 0xFFFE0000u); }
__device__ __forceinline__ void wg_fence() { asm volatile("wgmma.fence.sync.aligned;" ::: "memory"); }
__device__ __forceinline__ void wg_commit() { asm volatile("wgmma.commit_group.sync.aligned;" ::: "memory"); }
template <int N>
__device__ __forceinline__ void wg_wait() { asm volatile("wgmma.wait_group.sync.aligned %0;" ::"n"(N) : "memory"); }
template <int N>
__device__ __forceinline__ void reg_fence(uint32_t (&d)[N]) {
#pragma unroll
    for (int i = 0; i < N; i++) asm volatile("" : "+r"(d[i])::"memory");
}
template <int N>
__device__ __forceinline__ void reg_fence(float (&d)[N]) {
#pragma unroll
    for (int i = 0; i < N; i++) asm volatile("" : "+f"(d[i])::"memory");
}
__host__ __device__ constexpr uint32_t desc_hi(uint32_t sbo, uint32_t swz) { return (sbo >> 4) | (swz << 30); }
__host__ __device__ constexpr uint32_t desc_off(uint32_t bytes, uint32_t lbo) { return (bytes >> 4) + ((lbo >> 4) << 16); }
__device__ __forceinline__ uint32_t pack_bf16(float lo, float hi) {
    uint32_t r;
    asm("cvt.rn.bf16x2.f32 %0, %1, %2;" : "=r"(r) : "f"(hi), "f"(lo));
    return r;
}
__device__ __forceinline__ uint32_t pack_bf16_relu(float lo, float hi) {
    uint32_t r;
    asm("cvt.rn.relu.bf16x2.f32 %0, %1, %2;" : "=r"(r) : "f"(hi), "f"(lo));
    return r;
}
__device__ __forceinline__ float dot2_bf16(uint32_t a, uint32_t b) {
    uint32_t r;
    asm("mul.rn.bf16x2 %0, %1, %2;" : "=r"(r) : "r"(a), "r"(b));
    return __uint_as_float(r << 16) + __uint_as_float(r & 0xFFFF0000u);
}
__device__ __forceinline__ float round_bf16(float v) { return __bfloat162float(__float2bfloat16_rn(v)); }

template <int TB, uint32_t AHI, uint32_t BHI>
__device__ __forceinline__ void wgmma_n64(float (&d)[32], uint32_t alo, uint32_t blo, int scale_d) {
    asm volatile(
        "{\n.reg .pred p;\n.reg .b64 da, db;\n"
        "setp.ne.b32 p, %34, 0;\nmov.b64 da, {%32, %36};\nmov.b64 db, {%33, %37};\n"
        "wgmma.mma_async.sync.aligned.m64n64k16.f32.bf16.bf16 "
        "{%0, %1, %2, %3, %4, %5, %6, %7, %8, %9, %10, %11, %12, %13, %14, %15, "
        "%16, %17, %18, %19, %20, %21, %22, %23, %24, %25, %26, %27, %28, %29, %30, %31}, "
        "da, db, p, 1, 1, 0, %35;\n}\n"
        : "+f"(d[0]), "+f"(d[1]), "+f"(d[2]), "+f"(d[3]), "+f"(d[4]), "+f"(d[5]), "+f"(d[6]), "+f"(d[7]),
          "+f"(d[8]), "+f"(d[9]), "+f"(d[10]), "+f"(d[11]), "+f"(d[12]), "+f"(d[13]), "+f"(d[14]), "+f"(d[15]),
          "+f"(d[16]), "+f"(d[17]), "+f"(d[18]), "+f"(d[19]), "+f"(d[20]), "+f"(d[21]), "+f"(d[22]), "+f"(d[23]),
          "+f"(d[24]), "+f"(d[25]), "+f"(d[26]), "+f"(d[27]), "+f"(d[28]), "+f"(d[29]), "+f"(d[30]), "+f"(d[31])
        : "r"(alo), "r"(blo), "r"(scale_d), "n"(TB), "n"(AHI), "n"(BHI));
}

template <int TB, uint32_t AHI, uint32_t BHI>
__device__ __forceinline__ void wgmma_n120(float (&d)[60], uint32_t alo, uint32_t blo, int scale_d) {
    asm volatile(
        "{\n.reg .pred p;\n.reg .b64 da, db;\n"
        "setp.ne.b32 p, %62, 0;\nmov.b64 da, {%60, %64};\nmov.b64 db, {%61, %65};\n"
        "wgmma.mma_async.sync.aligned.m64n120k16.f32.bf16.bf16 "
        "{%0, %1, %2, %3, %4, %5, %6, %7, %8, %9, %10, %11, %12, %13, %14, %15, "
        "%16, %17, %18, %19, %20, %21, %22, %23, %24, %25, %26, %27, %28, %29, %30, %31, "
        "%32, %33, %34, %35, %36, %37, %38, %39, %40, %41, %42, %43, %44, %45, %46, %47, "
        "%48, %49, %50, %51, %52, %53, %54, %55, %56, %57, %58, %59}, "
        "da, db, p, 1, 1, 0, %63;\n}\n"
        : "+f"(d[0]), "+f"(d[1]), "+f"(d[2]), "+f"(d[3]), "+f"(d[4]), "+f"(d[5]), "+f"(d[6]), "+f"(d[7]),
          "+f"(d[8]), "+f"(d[9]), "+f"(d[10]), "+f"(d[11]), "+f"(d[12]), "+f"(d[13]), "+f"(d[14]), "+f"(d[15]),
          "+f"(d[16]), "+f"(d[17]), "+f"(d[18]), "+f"(d[19]), "+f"(d[20]), "+f"(d[21]), "+f"(d[22]), "+f"(d[23]),
          "+f"(d[24]), "+f"(d[25]), "+f"(d[26]), "+f"(d[27]), "+f"(d[28]), "+f"(d[29]), "+f"(d[30]), "+f"(d[31]),
          "+f"(d[32]), "+f"(d[33]), "+f"(d[34]), "+f"(d[35]), "+f"(d[36]), "+f"(d[37]), "+f"(d[38]), "+f"(d[39]),
          "+f"(d[40]), "+f"(d[41]), "+f"(d[42]), "+f"(d[43]), "+f"(d[44]), "+f"(d[45]), "+f"(d[46]), "+f"(d[47]),
          "+f"(d[48]), "+f"(d[49]), "+f"(d[50]), "+f"(d[51]), "+f"(d[52]), "+f"(d[53]), "+f"(d[54]), "+f"(d[55]),
          "+f"(d[56]), "+f"(d[57]), "+f"(d[58]), "+f"(d[59])
        : "r"(alo), "r"(blo), "r"(scale_d), "n"(TB), "n"(AHI), "n"(BHI));
}

template <int TB, uint32_t AHI, uint32_t BHI>
__device__ __forceinline__ void wgmma_n128(float (&d)[32], float (&e)[32], uint32_t alo, uint32_t blo, int scale_d) {
    asm volatile(
        "{\n.reg .pred p;\n.reg .b64 da, db;\n"
        "setp.ne.b32 p, %66, 0;\nmov.b64 da, {%64, %68};\nmov.b64 db, {%65, %69};\n"
        "wgmma.mma_async.sync.aligned.m64n128k16.f32.bf16.bf16 "
        "{%0, %1, %2, %3, %4, %5, %6, %7, %8, %9, %10, %11, %12, %13, %14, %15, "
        "%16, %17, %18, %19, %20, %21, %22, %23, %24, %25, %26, %27, %28, %29, %30, %31, "
        "%32, %33, %34, %35, %36, %37, %38, %39, %40, %41, %42, %43, %44, %45, %46, %47, "
        "%48, %49, %50, %51, %52, %53, %54, %55, %56, %57, %58, %59, %60, %61, %62, %63}, "
        "da, db, p, 1, 1, 0, %67;\n}\n"
        : "+f"(d[0]), "+f"(d[1]), "+f"(d[2]), "+f"(d[3]), "+f"(d[4]), "+f"(d[5]), "+f"(d[6]), "+f"(d[7]),
          "+f"(d[8]), "+f"(d[9]), "+f"(d[10]), "+f"(d[11]), "+f"(d[12]), "+f"(d[13]), "+f"(d[14]), "+f"(d[15]),
          "+f"(d[16]), "+f"(d[17]), "+f"(d[18]), "+f"(d[19]), "+f"(d[20]), "+f"(d[21]), "+f"(d[22]), "+f"(d[23]),
          "+f"(d[24]), "+f"(d[25]), "+f"(d[26]), "+f"(d[27]), "+f"(d[28]), "+f"(d[29]), "+f"(d[30]), "+f"(d[31]),
          "+f"(e[0]), "+f"(e[1]), "+f"(e[2]), "+f"(e[3]), "+f"(e[4]), "+f"(e[5]), "+f"(e[6]), "+f"(e[7]),
          "+f"(e[8]), "+f"(e[9]), "+f"(e[10]), "+f"(e[11]), "+f"(e[12]), "+f"(e[13]), "+f"(e[14]), "+f"(e[15]),
          "+f"(e[16]), "+f"(e[17]), "+f"(e[18]), "+f"(e[19]), "+f"(e[20]), "+f"(e[21]), "+f"(e[22]), "+f"(e[23]),
          "+f"(e[24]), "+f"(e[25]), "+f"(e[26]), "+f"(e[27]), "+f"(e[28]), "+f"(e[29]), "+f"(e[30]), "+f"(e[31])
        : "r"(alo), "r"(blo), "r"(scale_d), "n"(TB), "n"(AHI), "n"(BHI));
}

template <int TB, uint32_t AHI, uint32_t BHI>
__device__ __forceinline__ void wgmma_n176(float (&d)[88], uint32_t alo, uint32_t blo, int scale_d) {
    asm volatile(
        "{\n.reg .pred p;\n.reg .b64 da, db;\n"
        "setp.ne.b32 p, %90, 0;\nmov.b64 da, {%88, %92};\nmov.b64 db, {%89, %93};\n"
        "wgmma.mma_async.sync.aligned.m64n176k16.f32.bf16.bf16 "
        "{%0, %1, %2, %3, %4, %5, %6, %7, %8, %9, %10, %11, %12, %13, %14, %15, "
        "%16, %17, %18, %19, %20, %21, %22, %23, %24, %25, %26, %27, %28, %29, %30, %31, "
        "%32, %33, %34, %35, %36, %37, %38, %39, %40, %41, %42, %43, %44, %45, %46, %47, "
        "%48, %49, %50, %51, %52, %53, %54, %55, %56, %57, %58, %59, %60, %61, %62, %63, "
        "%64, %65, %66, %67, %68, %69, %70, %71, %72, %73, %74, %75, %76, %77, %78, %79, "
        "%80, %81, %82, %83, %84, %85, %86, %87}, "
        "da, db, p, 1, 1, 0, %91;\n}\n"
        : "+f"(d[0]), "+f"(d[1]), "+f"(d[2]), "+f"(d[3]), "+f"(d[4]), "+f"(d[5]), "+f"(d[6]), "+f"(d[7]),
          "+f"(d[8]), "+f"(d[9]), "+f"(d[10]), "+f"(d[11]), "+f"(d[12]), "+f"(d[13]), "+f"(d[14]), "+f"(d[15]),
          "+f"(d[16]), "+f"(d[17]), "+f"(d[18]), "+f"(d[19]), "+f"(d[20]), "+f"(d[21]), "+f"(d[22]), "+f"(d[23]),
          "+f"(d[24]), "+f"(d[25]), "+f"(d[26]), "+f"(d[27]), "+f"(d[28]), "+f"(d[29]), "+f"(d[30]), "+f"(d[31]),
          "+f"(d[32]), "+f"(d[33]), "+f"(d[34]), "+f"(d[35]), "+f"(d[36]), "+f"(d[37]), "+f"(d[38]), "+f"(d[39]),
          "+f"(d[40]), "+f"(d[41]), "+f"(d[42]), "+f"(d[43]), "+f"(d[44]), "+f"(d[45]), "+f"(d[46]), "+f"(d[47]),
          "+f"(d[48]), "+f"(d[49]), "+f"(d[50]), "+f"(d[51]), "+f"(d[52]), "+f"(d[53]), "+f"(d[54]), "+f"(d[55]),
          "+f"(d[56]), "+f"(d[57]), "+f"(d[58]), "+f"(d[59]), "+f"(d[60]), "+f"(d[61]), "+f"(d[62]), "+f"(d[63]),
          "+f"(d[64]), "+f"(d[65]), "+f"(d[66]), "+f"(d[67]), "+f"(d[68]), "+f"(d[69]), "+f"(d[70]), "+f"(d[71]),
          "+f"(d[72]), "+f"(d[73]), "+f"(d[74]), "+f"(d[75]), "+f"(d[76]), "+f"(d[77]), "+f"(d[78]), "+f"(d[79]),
          "+f"(d[80]), "+f"(d[81]), "+f"(d[82]), "+f"(d[83]), "+f"(d[84]), "+f"(d[85]), "+f"(d[86]), "+f"(d[87])
        : "r"(alo), "r"(blo), "r"(scale_d), "n"(TB), "n"(AHI), "n"(BHI));
}

template <int TB, uint32_t AHI, uint32_t BHI>
__device__ __forceinline__ void wgmma_n256(float (&d)[32], float (&e)[32], float (&f)[64], uint32_t alo, uint32_t blo, int scale_d) {
    asm volatile(
        "{\n.reg .pred p;\n.reg .b64 da, db;\n"
        "setp.ne.b32 p, %130, 0;\nmov.b64 da, {%128, %132};\nmov.b64 db, {%129, %133};\n"
        "wgmma.mma_async.sync.aligned.m64n256k16.f32.bf16.bf16 "
        "{%0, %1, %2, %3, %4, %5, %6, %7, %8, %9, %10, %11, %12, %13, %14, %15, "
        "%16, %17, %18, %19, %20, %21, %22, %23, %24, %25, %26, %27, %28, %29, %30, %31, "
        "%32, %33, %34, %35, %36, %37, %38, %39, %40, %41, %42, %43, %44, %45, %46, %47, "
        "%48, %49, %50, %51, %52, %53, %54, %55, %56, %57, %58, %59, %60, %61, %62, %63, "
        "%64, %65, %66, %67, %68, %69, %70, %71, %72, %73, %74, %75, %76, %77, %78, %79, "
        "%80, %81, %82, %83, %84, %85, %86, %87, %88, %89, %90, %91, %92, %93, %94, %95, "
        "%96, %97, %98, %99, %100, %101, %102, %103, %104, %105, %106, %107, %108, %109, %110, %111, "
        "%112, %113, %114, %115, %116, %117, %118, %119, %120, %121, %122, %123, %124, %125, %126, %127}, "
        "da, db, p, 1, 1, 0, %131;\n}\n"
        : "+f"(d[0]), "+f"(d[1]), "+f"(d[2]), "+f"(d[3]), "+f"(d[4]), "+f"(d[5]), "+f"(d[6]), "+f"(d[7]),
          "+f"(d[8]), "+f"(d[9]), "+f"(d[10]), "+f"(d[11]), "+f"(d[12]), "+f"(d[13]), "+f"(d[14]), "+f"(d[15]),
          "+f"(d[16]), "+f"(d[17]), "+f"(d[18]), "+f"(d[19]), "+f"(d[20]), "+f"(d[21]), "+f"(d[22]), "+f"(d[23]),
          "+f"(d[24]), "+f"(d[25]), "+f"(d[26]), "+f"(d[27]), "+f"(d[28]), "+f"(d[29]), "+f"(d[30]), "+f"(d[31]),
          "+f"(e[0]), "+f"(e[1]), "+f"(e[2]), "+f"(e[3]), "+f"(e[4]), "+f"(e[5]), "+f"(e[6]), "+f"(e[7]),
          "+f"(e[8]), "+f"(e[9]), "+f"(e[10]), "+f"(e[11]), "+f"(e[12]), "+f"(e[13]), "+f"(e[14]), "+f"(e[15]),
          "+f"(e[16]), "+f"(e[17]), "+f"(e[18]), "+f"(e[19]), "+f"(e[20]), "+f"(e[21]), "+f"(e[22]), "+f"(e[23]),
          "+f"(e[24]), "+f"(e[25]), "+f"(e[26]), "+f"(e[27]), "+f"(e[28]), "+f"(e[29]), "+f"(e[30]), "+f"(e[31]),
          "+f"(f[0]), "+f"(f[1]), "+f"(f[2]), "+f"(f[3]), "+f"(f[4]), "+f"(f[5]), "+f"(f[6]), "+f"(f[7]),
          "+f"(f[8]), "+f"(f[9]), "+f"(f[10]), "+f"(f[11]), "+f"(f[12]), "+f"(f[13]), "+f"(f[14]), "+f"(f[15]),
          "+f"(f[16]), "+f"(f[17]), "+f"(f[18]), "+f"(f[19]), "+f"(f[20]), "+f"(f[21]), "+f"(f[22]), "+f"(f[23]),
          "+f"(f[24]), "+f"(f[25]), "+f"(f[26]), "+f"(f[27]), "+f"(f[28]), "+f"(f[29]), "+f"(f[30]), "+f"(f[31]),
          "+f"(f[32]), "+f"(f[33]), "+f"(f[34]), "+f"(f[35]), "+f"(f[36]), "+f"(f[37]), "+f"(f[38]), "+f"(f[39]),
          "+f"(f[40]), "+f"(f[41]), "+f"(f[42]), "+f"(f[43]), "+f"(f[44]), "+f"(f[45]), "+f"(f[46]), "+f"(f[47]),
          "+f"(f[48]), "+f"(f[49]), "+f"(f[50]), "+f"(f[51]), "+f"(f[52]), "+f"(f[53]), "+f"(f[54]), "+f"(f[55]),
          "+f"(f[56]), "+f"(f[57]), "+f"(f[58]), "+f"(f[59]), "+f"(f[60]), "+f"(f[61]), "+f"(f[62]), "+f"(f[63])
        : "r"(alo), "r"(blo), "r"(scale_d), "n"(TB), "n"(AHI), "n"(BHI));
}


template <int MAP>
__global__ void __cluster_dims__(2, 1, 1) __launch_bounds__(384, 1) fused_kernel(const __grid_constant__ Params p) {
    extern __shared__ uint8_t smem_raw[];
    const uint32_t base = (smem_u32(smem_raw) + 1023u) & ~1023u;
    const uint32_t bars = base + OFF_BAR;
    auto bar = [&](int i) { return bars + 8u * i; };
    const int warp = threadIdx.x >> 5, lane = threadIdx.x & 31;
    int role = blockIdx.x >> 1;
    if (MAP == 1) {
        const int c = role;
        const int g = c < 4 ? 0 : c < 36 ? (c - 4) & 7 : 1 + (c - 36) % 7;
        const int r = c < 4 ? 4 + c : c < 36 ? (c - 4) >> 3 : 4 + (c - 36) / 7;
        role = ((g & 1) * 8 + r) * 4 + (g >> 1);
    }
    const bool extra = blockIdx.x >= NCTA;
    const int bid = extra ? blockIdx.x : role * 2 + (blockIdx.x & 1);
    constexpr int ABN = 120;
    constexpr uint32_t XW = 8192, XR = 8 * XW;
    auto extra_fill = [&](int f) {
        const int tt = ((bid - NCTA) >> 1) * 8 + 2 * (f >> 3) + (bid & 1), kk = f & 7, slot = f % 5;
        const uint32_t fb = bar(BAR_FULL_A + slot);
        const int nw = f < 2 ? 1 : f < 5 ? 2 : 0;
        mbar_expect_tx(fb, 16384 + nw * 8192);
        tma_load_2d(base + XR + slot * A_BYTES, &p.x, 64 * kk, 128 * tt, fb);
        for (int i = 0; i < nw; i++) {
            const int kw = kk + 3 * i;
            tma_load_2d(base + kw * XW, &p.hr32, 64 * kw, 480, fb);
            tma_load_2d(base + kw * XW + 4096, &p.hi32, 64 * kw, 480, fb);
        }
    };
    const int nh = bid & 1, kq = (bid >> 1) & 3, t = bid >> 3, j = bid & 7;
    const int kh = kq & 1, km = kq >> 1;
    const CUtensorMap* th = (j & 4) ? &p.hi : &p.hr;
    auto x_bar = [&](int f) { return bar(f < 6 ? BAR_FULL_A + f : BAR_FULL_X + f - 6); };
    auto x_fill = [&](int f) {
        mbar_expect_tx(x_bar(f), A_BYTES);
        tma_load_2d(base + f * A_BYTES, &p.x, 64 * f, 128 * t, x_bar(f));
    };
    auto p1_fill = [&](int f) {
        const uint32_t dst = base + OFF_P + (f & 3) * P_BYTES, fb = bar(BAR_FULL_P + (f & 3));
        const int kk = f & 7;
        if (f < 8) {
            mbar_expect_tx(fb, ABN * 128);
            tma_load_2d(dst, th, 64 * kk, ABN * (j & 3), fb);
        } else {
            mbar_expect_tx(fb, 24576);
            for (int q = 0; q < 3; q++) tma_load_2d(dst + q * 8192, &p.w1, HSL * j + 64 * q, 64 * kk, fb);
        }
    };
    if (threadIdx.x == 0) {
        mbar_init(bar(BAR_FULL_A), 1); mbar_init(bar(BAR_FULL_P), 1);
        if (!extra) { x_fill(0); p1_fill(0); } else extra_fill(0);
    } else if (threadIdx.x == 32) {
        for (int i = 1; i < NA; i++) mbar_init(bar(BAR_FULL_A + i), 1);
        mbar_init(bar(BAR_FULL_X), 1); mbar_init(bar(BAR_FULL_X + 1), 1);
        for (int i = 1; i < 4; i++) mbar_init(bar(BAR_FULL_P + i), 1);
        for (int i = 0; i < NA; i++) mbar_init(bar(BAR_EMPTY_A + i), 8);
        for (int i = 0; i < 4; i++) {
            mbar_init(bar(BAR_EMPTY_P + i), 8);
            mbar_init(bar(BAR_FULL_B + i), 1); mbar_init(bar(BAR_EMPTY_B + i), 8);
        }
        prefetch_tmap(&p.w1);
    } else if (threadIdx.x == 64) {
        mbar_init(bar(BAR_SIG_AB), 8); mbar_init(bar(BAR_SIG_H), 8); mbar_init(bar(BAR_H_READY), 1);
        for (int i = 0; i < 8; i++) mbar_init(bar(BAR_AB_T + i), 1);
        mbar_init(bar(BAR_EPOCH), 1); mbar_init(bar(BAR_B0), 1);
    }
    __syncthreads();
    if (warp < 4) {
        asm volatile("setmaxnreg.dec.sync.aligned.u32 40;");
        if (extra) {
            const int e = bid - NCTA;
            if (warp == 0 && lane == 0) {
#pragma unroll 1
                for (int f = 1; f < 32; f++) {
                    mbar_wait(bar(BAR_EMPTY_A + f % 5), ((f / 5) & 1) ^ 1);
                    extra_fill(f);
                }
            } else if (warp == 2 && lane == 0) {
#pragma unroll 1
                for (int u = 0; u < 4; u++) {
                    const int tt = (e >> 1) * 8 + 2 * u + (e & 1);
                    mbar_wait(bar(BAR_EMPTY_B + u), 0);
                    fence_proxy_async_global();
                    asm volatile("fence.acq_rel.gpu;" ::: "memory");
                    red_relaxed_add(&g_cnt_ab[tt * 32], 1);
                    red_relaxed_add(&g_cnt_ab[(16 + tt) * 32], 1);
                }
            }
        } else if (warp == 0 && lane == 0) {
            x_fill(1); p1_fill(1); x_fill(2); p1_fill(2); x_fill(3); p1_fill(3);
#pragma unroll 1
            for (int f = 4; f < 8; f++) x_fill(f);
            const CUtensorMap* tc = km ? &p.ci : &p.cr;
            int slot = 0; uint32_t ph = 0;
#pragma unroll 1
            for (int i = 0; i < 27; i++) {
                const uint32_t dst = base + slot * A_BYTES, fb = bar(BAR_FULL_A + slot);
                if (i == DEFER_A) mbar_wait(bar(BAR_B0), 0);
                mbar_wait(bar(BAR_EMPTY_A + slot), ph);
                if (i < 16) {
                    mbar_expect_tx(fb, A_BYTES);
                    tma_load_2d(dst, tc, kh * 1024 + 64 * i, 128 * t, fb);
                } else {
                    if (i == 16) { mbar_wait(bar(BAR_H_READY), 0); fence_proxy_async_global(); }
                    const uint32_t bytes = i < 26 ? A_BYTES : 12288u;
                    mbar_expect_tx(fb, bytes);
                    bulk_load(dst, g_h + (size_t)(t * FG + kh * 86 + 8 * (i - 16)) * 128, bytes, fb);
                }
                if (++slot == NA) { slot = 0; ph ^= 1; }
            }
        } else if (warp == 1 && lane == 0) {
#pragma unroll 1
            for (int f = 4; f < 16; f++) {
                mbar_wait(bar(BAR_EMPTY_P + (f & 3)), ((f >> 2) & 1) ^ 1);
                p1_fill(f);
            }
#pragma unroll 1
            for (int f = 0; f < 22; f++) {
                const int bs = f & 3;
                const uint32_t dst = base + off_b(bs), fb = bar(BAR_FULL_B + bs);
                mbar_wait(bar(BAR_EMPTY_B + bs), (f >> 2) & 1);
                if (f < 16) {
                    if (!(f & 1)) { mbar_wait(bar(BAR_AB_T + (f >> 1)), 0); fence_proxy_async_global(); }
                    mbar_expect_tx(fb, B_BYTES);
                    const uint4* src = g_ab + (size_t)((km * 32 + kh * 16 + f) * 8 + nh * 4) * 512;
                    bulk_load(dst, src + km * 1024, 16384, fb);
                    bulk_load(dst + 16384, src + (km ^ 1) * 1024, 16384, fb);
                    if (f == 2) mbar_arrive(bar(BAR_B0));
                } else {
                    const int nsub = f < 21 ? 2 : 1;
                    mbar_expect_tx(fb, nsub * 16384);
                    for (int s = 0; s < nsub; s++)
                        for (int q = 0; q < 2; q++)
                            tma_load_2d(dst + s * 16384 + q * 8192, &p.w2, nh * 256 + km * 128 + q * 64, kh * 688 + 128 * (f - 16) + 64 * s, fb);
                }
            }
        } else if (warp == 2 && lane == 0) {
            const uint32_t ep = g_epoch[bid] + 1;
            g_epoch[bid] = ep;
            asm volatile("st.shared.u32 [%0], %1;" ::"r"(base + OFF_EPOCH), "r"(ep) : "memory");
            mbar_arrive(bar(BAR_EPOCH));
            prefetch_tmap(km ? &p.ci : &p.cr);
            prefetch_tmap(&p.w2);
            mbar_wait(bar(BAR_SIG_AB), 0);
            fence_proxy_async_global();
            red_release_add(&g_cnt_ab[((j >> 2) * 16 + t) * 32], 1);
            mbar_wait(bar(BAR_SIG_H), 0);
            fence_proxy_async_global();
            red_release_add(&g_cnt_h[t * 32], 1);
            l2_prefetch((const uint8_t*)p.pw2 + bid * 11008, 11008);
            wait_counter(&g_cnt_h[t * 32], 8 * ep);
            mbar_arrive(bar(BAR_H_READY));
        } else if (warp == 3) {
            const long long t0 = clock64();
            while (clock64() - t0 < 1000) {}
            if (lane == 0 && t < 4) l2_prefetch_tile(th, 64 * (4 + t), ABN * (j & 3));
            mbar_wait(x_bar(6), 0);
            if (lane == 0) l2_prefetch((const uint8_t*)p.pw1 + bid * 11008, 11008);
            if (lane == 0 && bid < 2) l2_prefetch(p.gate, 1024);
            mbar_wait(bar(BAR_EPOCH), 0);
            uint32_t ep;
            asm volatile("ld.shared.u32 %0, [%1];" : "=r"(ep) : "r"(base + OFF_EPOCH) : "memory");
            const uint32_t* cnt = &g_cnt_ab[(km * 16 + kh * 8 + (lane & 7)) * 32];
            ep *= 5;
            bool done = lane >= 8 || (int32_t)(ld_acquire(cnt) - ep) >= 0;
            if (done && lane < 8) mbar_arrive(bar(BAR_AB_T + lane));
            mbar_wait(bar(BAR_EMPTY_A + POLL_AT), 0);
            for (uint32_t n = 0; n < SPIN_LIMIT && !__all_sync(0xffffffffu, done); n++) {
                if (!done && (int32_t)(ld_acquire(cnt) - ep) >= 0) {
                    mbar_arrive(bar(BAR_AB_T + lane));
                    done = true;
                }
                __nanosleep(n < 40 ? POLL_NS : POLL_SLOW_NS);
            }
        }
    } else {
        asm volatile("setmaxnreg.inc.sync.aligned.u32 232;");
        const int w = __shfl_sync(0xffffffffu, (warp - 4) >> 2, 0), q = warp & 3, ctid = threadIdx.x - 128;
        constexpr uint32_t H_K128 = desc_hi(1024, 1);
        constexpr uint32_t H_MN128 = desc_hi(1024, 1);
        constexpr uint32_t H_AB = desc_hi(1024, 0);
        constexpr uint32_t H_H = desc_hi(128, 0);
        const uint32_t d0 = (base & 0x3FFFFu) >> 4;
        auto release = [&](int b) { if (lane == 0) mbar_arrive(bar(b)); };
        if (extra) {
            const int e = bid - NCTA;
            float acc[32];
            uint32_t pk[16];
            int slot = 0, prev = 0; uint32_t ph = 0;
            auto flush = [&](int u) {
                const int tt = (e >> 1) * 8 + 2 * u + (e & 1);
                uint32_t* dst = (uint32_t*)(g_ab + (size_t)((2 * tt + w) * 8) * 512) + 60 * 256 + (2 * q) * 32 + lane;
#pragma unroll
                for (int i = 0; i < 16; i++)
                    dst[(i >> 3) * (32 * 8 * 2048) + ((i >> 1) & 3) * 256 + (i & 1) * 32] = pk[i];
                __syncwarp();
                release(BAR_EMPTY_B + u);
            };
#pragma unroll 1
            for (int u = 0; u < 4; u++) {
#pragma unroll
                for (int kk = 0; kk < 8; kk++) {
                    mbar_wait(bar(BAR_FULL_A + slot), ph);
                    wg_fence();
#pragma unroll
                    for (int i = 0; i < 4; i++)
                        wgmma_n64<0, H_K128, H_K128>(acc, d0 + w * 512 + slot * (A_BYTES >> 4) + desc_off(XR + i * 32, 16), d0 + desc_off(kk * XW + i * 32, 16), (kk | i) != 0);
                    wg_commit();
                    if (kk > 0) { wg_wait<1>(); release(BAR_EMPTY_A + prev); }
                    if (kk == 0 && u > 0) flush(u - 1);
                    prev = slot;
                    if (++slot == 5) { slot = 0; ph ^= 1; }
                }
                wg_wait<0>();
                release(BAR_EMPTY_A + prev);
                reg_fence(acc);
#pragma unroll
                for (int i = 0; i < 16; i++) pk[i] = pack_bf16(acc[2 * i], acc[2 * i + 1]);
                reg_fence(pk);
            }
            flush(3);
            return;
        }
        float g0 = 0.f, g1 = 0.f, o0 = 0.f, o1 = 0.f;
        auto gate = [&](float z0, float z1) {
            g0 = round_bf16(__fdividef(1.f, 1.f + __expf(-round_bf16(z0))));
            g1 = round_bf16(__fdividef(1.f, 1.f + __expf(-round_bf16(z1))));
            o0 = round_bf16(1.f - g0); o1 = round_bf16(1.f - g1);
        };
        float cO[32], cS[32], cX[64];
        uint32_t hpk[44];
        const int zrow = 128 * t + 16 * j + 2 * (warp - 4);
        uint4 zx[4], zg[2];
        {
            constexpr int NPK = ABN / 4;
            float accAB[60], accH[88];
            uint32_t* abdst = (uint32_t*)(g_ab + (size_t)(((j >> 2) * 32 + 2 * t + w) * 8) * 512) + (j & 3) * (ABN / 8) * 256 + (2 * q) * 32 + lane;
            uint32_t abpk[NPK];
            const bool fast = (t & 7) < AB_FAST_TILES;
            auto ab_store = [&](int slotno) {
#pragma unroll
                for (int e = 0; e < NPK; e++) {
                    const bool inf = e * (4 * AB_FAST_STEPS + AB_PRE) / NPK == slotno, ins = e * (4 * AB_SLOW_STEPS + AB_PRE) / NPK == slotno;
                    if ((inf && ins) || (inf && fast) || (ins && !fast)) abdst[(e >> 1) * 256 + (e & 1) * 32] = abpk[e];
                }
            };
#pragma unroll
            for (int s = 0; s < 16; s++) {
                const int kk = s & 7;
                const bool isab = s < 8;
                if (isab) mbar_wait(x_bar(kk), 0);
                mbar_wait(bar(BAR_FULL_P + (s & 3)), (s >> 2) & 1);
                wg_fence();
#pragma unroll
                for (int i = 0; i < 4; i++) {
                    const uint32_t da = d0 + w * 512 + desc_off(kk * A_BYTES + i * 32, 16);
                    if (isab) wgmma_n120<0, H_K128, H_K128>(accAB, da, d0 + desc_off(OFF_P + (s & 3) * P_BYTES + i * 32, 16), (kk | i) != 0);
                    else wgmma_n176<1, H_K128, H_MN128>(accH, da, d0 + desc_off(OFF_P + (s & 3) * P_BYTES + i * 2048, 8192), (kk | i) != 0);
                    if (s >= 9 && s < 9 + AB_SLOW_STEPS) ab_store(AB_PRE + (s - 9) * 4 + i);
                }
                wg_commit();
                if (s > 0) {
                    wg_wait<1>();
                    if (s - 1 < 12) release(BAR_EMPTY_P + ((s - 1) & 3));
                    if (s - 1 >= 13) release(BAR_EMPTY_B + (s - 1) - 13);
                    if (s - 1 >= 8 && s - 1 < 14) release(BAR_EMPTY_A + s - 9);
                }
                if ((s == 8 + AB_FAST_STEPS && fast) || (s == 8 + AB_SLOW_STEPS && !fast)) { __syncwarp(); release(BAR_SIG_AB); }
                if (s == 8) {
                    reg_fence(accAB);
#pragma unroll
                    for (int e = 0; e < NPK; e++) abpk[e] = pack_bf16(accAB[2 * e], accAB[2 * e + 1]);
                    reg_fence(abpk);
#pragma unroll
                    for (int u = 0; u < AB_PRE; u++) ab_store(u);
                }
            }
            wg_wait<0>();
            release(BAR_EMPTY_B + 2);
            release(BAR_EMPTY_B + 3);
            reg_fence(accH);
#pragma unroll
            for (int i = 0; i < 22; i++) {
                hpk[2 * i] = pack_bf16_relu(accH[4 * i], accH[4 * i + 1]);
                hpk[2 * i + 1] = pack_bf16_relu(accH[4 * i + 2], accH[4 * i + 3]);
            }
            reg_fence(hpk);
        }
        int sA = 0; uint32_t phA = 1;
        int pA = 0;
        mbar_wait(bar(BAR_EPOCH), 0);
        uint32_t tag;
        asm volatile("ld.shared.u32 %0, [%1];" : "=r"(tag) : "r"(base + OFF_EPOCH) : "memory");
        tag = (tag & 1u) << 16;
        uint4* pdst = g_part + (size_t)(bid ^ 4) * 2048 + ctid;
        uint4* orow = (uint4*)(p.pout + (size_t)(128 * t + 64 * w + 16 * q + (lane >> 3)) * DM + nh * 256 + kq * 64) + (lane & 7);
        uint32_t* hdst = (uint32_t*)(g_h + (size_t)(t * FG + 22 * j) * 128) + (8 * w + 2 * q) * 32 + lane;
        auto c_step = [&](int i, bool trickle) {
            const uint32_t da = d0 + w * 512 + sA * (A_BYTES >> 4) + desc_off(0, 16), db = d0 + (off_b(i & 3) >> 4) + desc_off(0, 128);
            mbar_wait(bar(BAR_FULL_A + sA), phA);
            mbar_wait(bar(BAR_FULL_B + (i & 3)), (i >> 2) & 1);
            wg_fence();
#pragma unroll
            for (int u = 0; u < 4; u++) {
                wgmma_n256<1, H_K128, H_AB>(cO, cS, cX, da + u * 2, db + u * 16, (i | u) != 0);
                if (trickle) {
#pragma unroll
                    for (int e = 0; e < 44; e++)
                        if (e * (4 * H_STEPS) / 44 == (i - H_START) * 4 + u) hdst[(e >> 1) * 512 + (e & 1) * 32] = hpk[e];
                }
            }
            wg_commit();
            if (i > 0) {
                wg_wait<1>();
                release(BAR_EMPTY_B + ((i - 1) & 3));
                release(BAR_EMPTY_A + pA);
            }
            if (trickle && i >= ZERO_STEP && i < ZERO_STEP + 4) orow[(i - ZERO_STEP) * 4 * (DM / 8)] = make_uint4(0u, 0u, 0u, 0u);
            if (trickle && i == Z_STEP) {
                float z[2];
#pragma unroll
                for (int r = 0; r < 2; r++) {
                    z[r] = 0.f;
#pragma unroll
                    for (int v = 0; v < 2; v++)
                        z[r] += (dot2_bf16(zx[2 * r + v].x, zg[v].x) + dot2_bf16(zx[2 * r + v].y, zg[v].y)) +
                                (dot2_bf16(zx[2 * r + v].z, zg[v].z) + dot2_bf16(zx[2 * r + v].w, zg[v].w));
                }
                float zz = (lane & 1) ? z[1] : z[0];
                zz += __shfl_xor_sync(0xffffffffu, (lane & 1) ? z[0] : z[1], 1);
#pragma unroll
                for (int m = 2; m < 32; m *= 2) zz += __shfl_xor_sync(0xffffffffu, zz, m);
                if (lane < 2) g_z[zrow + lane] = zz;
            }
            if (trickle && i == Z_STEP - 2) {
#pragma unroll
                for (int v = 0; v < 4; v++) zx[v] = ldg128((const uint4*)(p.px + (size_t)(zrow + (v >> 1)) * DM) + (v & 1) * 32 + lane);
                zg[0] = ldg128((const uint4*)p.gate + lane);
                zg[1] = ldg128((const uint4*)p.gate + 32 + lane);
            }
            if (trickle && i == H_START + H_STEPS - 1) { __syncwarp(); release(BAR_SIG_H); }
            if (!trickle) {
                if (i == 14) {
                    mbar_wait(bar(BAR_H_READY), 0);
                    g0 = __ldcg(&g_z[128 * t + 64 * w + 16 * q + (lane >> 2)]);
                    g1 = __ldcg(&g_z[128 * t + 64 * w + 16 * q + 8 + (lane >> 2)]);
                }
                if (i == 15) gate(g0, g1);
            }
            pA = sA;
            if (++sA == NA) { sA = 0; phA ^= 1; }
        };
#pragma unroll
        for (int i = 0; i < H_START + H_STEPS; i++) c_step(i, true);
#pragma unroll 1
        for (int i = H_START + H_STEPS; i < 16; i++) c_step(i, false);
        static_assert(H_START + H_STEPS <= 14 && ZERO_STEP + 4 <= H_START + H_STEPS && Z_STEP < H_START + H_STEPS, "");
        float hO[32], hS[32];
        uint32_t xpk[32];
        uint4 rs[4], ro[4];
        const uint4* psrc = g_part + (size_t)bid * 2048 + ctid;
        const float k0 = km ? -g0 : g0, k1 = km ? -g1 : g1;
        auto p_io = [&](int slotno) {
#pragma unroll
            for (int o = 0; o < 8; o++) {
                const int e = o ^ 4;
                if (o * X_SLOTS / 8 == slotno) st_relaxed_v4(pdst + e * 256, xpk[4 * e], xpk[4 * e + 1], xpk[4 * e + 2], xpk[4 * e + 3]);
                if (o < 4 && o * X_SLOTS / 8 + X_DELAY == slotno) rs[o] = ld_relaxed_v4(psrc + e * 256);
                if (o >= 4 && X_LOAD2 + 2 * (o - 4) == slotno) ro[o - 4] = ld_relaxed_v4(psrc + e * 256);
            }
        };
        auto fold4 = [&](float (&c)[32], int v, const uint4 (&r)[4]) {
            const uint32_t wa = (v & 1) ? r[v >> 1].z : r[v >> 1].x, wb = (v & 1) ? r[v >> 1].w : r[v >> 1].y;
            c[4 * v + 0] = k0 * (c[4 * v + 0] - lo_f(wa)); c[4 * v + 1] = k0 * (c[4 * v + 1] - hi_f(wa));
            c[4 * v + 2] = k1 * (c[4 * v + 2] - lo_f(wb)); c[4 * v + 3] = k1 * (c[4 * v + 3] - hi_f(wb));
#pragma unroll
            for (int u = 0; u < 4; u++) asm volatile("" : "+f"(c[4 * v + u])::"memory");
        };
        static_assert(3 * X_SLOTS / 8 + X_DELAY <= 32 && X_LOAD2 > 32 && X_LOAD2 + 6 <= 39, "");
#pragma unroll
        for (int i = 0; i < 11; i++) {
            const int fb = i >> 1;
            const uint32_t da = d0 + w * 64 + sA * (A_BYTES >> 4) + desc_off(0, 2048), db = d0 + desc_off(off_b(fb & 3) + (i & 1) * 16384, 8192);
            mbar_wait(bar(BAR_FULL_A + sA), phA);
            if (!(i & 1)) mbar_wait(bar(BAR_FULL_B + (fb & 3)), (fb >> 2) & 1);
            wg_fence();
#pragma unroll
            for (int u = 0; u < (i < 10 ? 4 : 3); u++) {
                wgmma_n128<1, H_H, H_MN128>(hO, hS, da + u * 256, db + u * 128, (i | u) != 0);
                if (i > 0) p_io(1 + (i - 1) * 4 + u);
                if (i >= 9) fold4(cS, (i - 9) * 4 + u, rs);
            }
            wg_commit();
            wg_wait<1>();
            if (i < 10) {
                release(BAR_EMPTY_A + pA);
                if (!(i & 1)) release(BAR_EMPTY_B + ((fb - 1) & 3));
            }
            if (i == 8) recv_tagged(rs, psrc + 4 * 256, tag);
            if (i == 0) {
                reg_fence(cO); reg_fence(cS); reg_fence(cX);
#pragma unroll
                for (int e = 0; e < 32; e++) xpk[e] = (pack_bf16(cX[2 * e], cX[2 * e + 1]) & ~TAG_BIT) | tag;
                reg_fence(xpk);
                p_io(0);
            }
            pA = sA;
            if (++sA == NA) { sA = 0; phA ^= 1; }
        }
        fold4(cS, 7, rs);
        recv_tagged(ro, psrc, tag);
#pragma unroll
        for (int v = 0; v < 8; v++) fold4(cO, v, ro);
        mbar_wait(bar(BAR_H_READY), 0);
        mbar_wait(bar(BAR_EMPTY_B + 2), 1);
        wg_wait<0>();
        reg_fence(hO); reg_fence(hS);
        {
            const uint32_t stg = base + off_b(2) + (warp - 4) * 4096;
            const int row = ((lane >> 3) & 1) * 8 + (lane & 7);
#pragma unroll
            for (int hf = 0; hf < 2; hf++) {
                float (&c)[32] = hf ? cS : cO;
                float (&h)[32] = hf ? hS : hO;
#pragma unroll
                for (int u = 0; u < 4; u++) {
                    uint32_t v[4];
#pragma unroll
                    for (int e = 0; e < 4; e++) {
                        const float o = (e & 1) ? o1 : o0;
                        v[e] = pack_bf16(fmaf(o, h[8 * u + 2 * e], c[8 * u + 2 * e]), fmaf(o, h[8 * u + 2 * e + 1], c[8 * u + 2 * e + 1]));
                    }
                    const int cc = 2 * u + (lane >> 4);
                    stmatrix_x4(stg + hf * 2048 + row * 128 + ((cc ^ (row & 7)) << 4), v[0], v[1], v[2], v[3]);
                }
                __syncwarp();
                uint4* dst = orow + (hf - kh) * 8;
#pragma unroll
                for (int u = 0; u < 4; u++) {
                    const int r = 4 * u + (lane >> 3);
                    const uint4 v = lds128(stg + hf * 2048 + r * 128 + (((lane & 7) ^ (r & 7)) << 4));
                    asm volatile("red.relaxed.gpu.global.add.noftz.v4.bf16x2 [%0], {%1, %2, %3, %4};"
                                 ::"l"(dst + u * 4 * (DM / 8)), "r"(v.x), "r"(v.y), "r"(v.z), "r"(v.w) : "memory");
                }
            }
        }
    }
}

__device__ __nv_bfloat16 g_fb[SEQ * (2 * DM + DFF)];
__global__ void fb_stage1(const __nv_bfloat16* x, const __nv_bfloat16* hr, const __nv_bfloat16* hi, const __nv_bfloat16* w1) {
    __shared__ float xs[DM];
    const int r = blockIdx.x;
    for (int d = threadIdx.x; d < DM; d += blockDim.x) xs[d] = __bfloat162float(x[r * DM + d]);
    __syncthreads();
    for (int c = threadIdx.x; c < 2 * DM + DFF; c += blockDim.x) {
        float s = 0.f;
        if (c < 2 * DM) {
            const __nv_bfloat16* m = (c < DM ? hr : hi) + (c & (DM - 1)) * DM;
            for (int d = 0; d < DM; d++) s += xs[d] * __bfloat162float(m[d]);
        } else {
            for (int d = 0; d < DM; d++) s += xs[d] * __bfloat162float(w1[d * DFF + c - 2 * DM]);
            s = fmaxf(s, 0.f);
        }
        g_fb[(size_t)r * (2 * DM + DFF) + c] = __float2bfloat16_rn(s);
    }
}
__global__ void fb_stage2(const __nv_bfloat16* x, const __nv_bfloat16* cr, const __nv_bfloat16* ci, const __nv_bfloat16* w2,
                          const __nv_bfloat16* gate, __nv_bfloat16* out) {
    const int r = blockIdx.x, c = threadIdx.x;
    float z = 0.f, y = 0.f, f = 0.f;
    for (int d = 0; d < DM; d++) z += round_bf16(__bfloat162float(x[r * DM + d]) * __bfloat162float(gate[d]));
    for (int s = 0; s < SEQ; s++) {
        const __nv_bfloat16* ab = g_fb + (size_t)s * (2 * DM + DFF);
        y += __bfloat162float(cr[(size_t)r * SEQ + s]) * __bfloat162float(ab[c]) - __bfloat162float(ci[(size_t)r * SEQ + s]) * __bfloat162float(ab[DM + c]);
    }
    for (int k = 0; k < DFF; k++) f += __bfloat162float(g_fb[(size_t)r * (2 * DM + DFF) + 2 * DM + k]) * __bfloat162float(w2[k * DM + c]);
    const float g = round_bf16(1.f / (1.f + __expf(-round_bf16(z))));
    out[r * DM + c] = __float2bfloat16_rn(g * y + round_bf16(1.f - g) * f);
}
__global__ void probe_kernel() {}

typedef CUresult (*EncodeFn)(CUtensorMap*, CUtensorMapDataType, cuuint32_t, void*, const cuuint64_t*, const cuuint64_t*,
                             const cuuint32_t*, const cuuint32_t*, CUtensorMapInterleave, CUtensorMapSwizzle,
                             CUtensorMapL2promotion, CUtensorMapFloatOOBfill);

bool make_map(EncodeFn enc, CUtensorMap* m, const void* ptr, uint64_t inner, uint64_t outer, uint32_t box_inner, uint32_t box_outer) {
    cuuint64_t dims[2] = {inner, outer};
    cuuint64_t strides[1] = {inner * 2};
    cuuint32_t box[2] = {box_inner, box_outer};
    cuuint32_t es[2] = {1, 1};
    return enc(m, CU_TENSOR_MAP_DATA_TYPE_BFLOAT16, 2, const_cast<void*>(ptr), dims, strides, box, es, CU_TENSOR_MAP_INTERLEAVE_NONE,
               CU_TENSOR_MAP_SWIZZLE_128B, CU_TENSOR_MAP_L2_PROMOTION_L2_128B, CU_TENSOR_MAP_FLOAT_OOB_FILL_NONE) == CUDA_SUCCESS;
}

template <class K>
int max_clusters(K kernel, int cluster, bool set_dim) {
    cudaLaunchConfig_t cfg = {};
    cfg.gridDim = dim3(NCTA);
    cfg.blockDim = dim3(384);
    cfg.dynamicSmemBytes = SMEM_BYTES;
    cudaLaunchAttribute at[1];
    at[0].id = cudaLaunchAttributeClusterDimension;
    at[0].val.clusterDim.x = cluster;
    at[0].val.clusterDim.y = 1;
    at[0].val.clusterDim.z = 1;
    cfg.attrs = at;
    cfg.numAttrs = set_dim ? 1 : 0;
    int n = 0;
    if (cudaFuncSetAttribute(kernel, cudaFuncAttributeMaxDynamicSharedMemorySize, SMEM_BYTES) != cudaSuccess ||
        cudaOccupancyMaxActiveClusters(&n, kernel, &cfg) != cudaSuccess) {
        (void)cudaGetLastError();
        return 0;
    }
    return n;
}

}

extern "C" void kernel_launch(void* const* d_in, const int* in_sizes, int n_in, void* d_out, int out_size) {
    (void)in_sizes; (void)n_in; (void)out_size;
    static Params prm;
    static const void* cached[10] = {};
    static int mode = -1;
    bool same = mode >= 0 && cached[9] == d_out;
    for (int i = 0; i < 9; i++) same = same && cached[i] == d_in[i];
    if (!same) {
        prm.px = (const __nv_bfloat16*)d_in[0];
        prm.pcr = (const __nv_bfloat16*)d_in[1];
        prm.pci = (const __nv_bfloat16*)d_in[2];
        prm.phr = (const __nv_bfloat16*)d_in[3];
        prm.phi = (const __nv_bfloat16*)d_in[4];
        prm.pw1 = (const __nv_bfloat16*)d_in[6];
        prm.pw2 = (const __nv_bfloat16*)d_in[7];
        prm.gate = (const __nv_bfloat16*)d_in[8];
        prm.pout = (__nv_bfloat16*)d_out;
        if (max_clusters(fused_kernel<0>, 2, false) >= NCTA / 2 + 2 && max_clusters(fused_kernel<1>, 2, false) >= NCTA / 2 + 2)
            mode = (max_clusters(probe_kernel, 2, true) == 66 && max_clusters(probe_kernel, 4, true) == 30 && max_clusters(probe_kernel, 8, true) == 15) ? 1 : 0;
        else
            mode = 2;
        void* fn = nullptr;
        cudaDriverEntryPointQueryResult qr;
        bool ok = cudaGetDriverEntryPoint("cuTensorMapEncodeTiled", &fn, cudaEnableDefault, &qr) == cudaSuccess && fn != nullptr;
        EncodeFn enc = (EncodeFn)fn;
        ok = ok && make_map(enc, &prm.x, prm.px, DM, SEQ, 64, 128) && make_map(enc, &prm.hr, prm.phr, DM, DM, 64, 120) &&
             make_map(enc, &prm.hi, prm.phi, DM, DM, 64, 120) &&
             make_map(enc, &prm.w1, prm.pw1, DFF, DM, 64, 64) && make_map(enc, &prm.cr, prm.pcr, SEQ, SEQ, 64, 128) &&
             make_map(enc, &prm.ci, prm.pci, SEQ, SEQ, 64, 128) && make_map(enc, &prm.w2, prm.pw2, DM, DFF, 64, 64) &&
             make_map(enc, &prm.hr32, prm.phr, DM, DM, 64, 32) && make_map(enc, &prm.hi32, prm.phi, DM, DM, 64, 32);
        (void)cudaGetLastError();
        if (!ok) mode = 2;
        for (int i = 0; i < 9; i++) cached[i] = d_in[i];
        cached[9] = d_out;
    }
    if (mode == 1) {
        fused_kernel<1><<<NCTA + 4, 384, SMEM_BYTES>>>(prm);
    } else if (mode == 0) {
        fused_kernel<0><<<NCTA + 4, 384, SMEM_BYTES>>>(prm);
    } else {
        fb_stage1<<<SEQ, 256>>>(prm.px, prm.phr, prm.phi, prm.pw1);
        fb_stage2<<<SEQ, DM>>>(prm.px, prm.pcr, prm.pci, prm.pw2, prm.gate, prm.pout);
    }
}
```
